```python
import torch

def _softmax(x, axis=-1):
    return torch.softmax(x, dim=axis)
def _gelu(x):
    return torch.nn.functional.gelu(x, approximate="tanh")
def _silu(x):
    return torch.nn.functional.silu(x)
def _sigmoid(x):
    return torch.sigmoid(x)
def _layernorm(x, axis=-1, eps=1e-5):
    m = x.mean(dim=axis, keepdim=True)
    v = x.var(dim=axis, keepdim=True, unbiased=False)
    return (x - m) / torch.sqrt(v + eps)
def _scatter_add(tgt, idx, src, axis=0):
    return tgt.clone().index_add_(axis, idx, src)
def _segment_sum(src, seg, n):
    out = torch.zeros((n,) + src.shape[1:], dtype=src.dtype)
    return out.index_add_(0, seg, src)
def _pad(x, pw):
    flat = tuple(v for pair in reversed(pw) for v in pair)
    return torch.nn.functional.pad(x, flat)

kernel_name = 'parallel_sum__gqa_block_cached__glu_gated_geglu__decode'

def setup_inputs():

    _w = (lambda a: (lambda t: t.to(torch.bfloat16) if t.is_floating_point() else t)(torch.as_tensor(a)))
    def _A_setup():
        B, Sq, D = 1, 1, 1024
        Hq, Hkv, Sk, Dh = 32, 4, 65536, 128
        assert Hq % Hkv == 0, (Hq, Hkv)
        return {
            "x": _w((lambda *s: torch.randn(*s, dtype=torch.bfloat16) * 0.05)(B, Sq, D)),
            "k_cache": _w((lambda *s: torch.randn(*s, dtype=torch.bfloat16) * 3.2)(B, Hkv, Sk, Dh)),
            "v_cache": _w((lambda *s: torch.randn(*s, dtype=torch.bfloat16) * 1.6)(B, Hkv, Sk, Dh)),
            "wq": _w((lambda *s: torch.randn(*s, dtype=torch.bfloat16) * 3.2)(D, Hq * Dh) * (D ** -0.5)),
            "wo": _w((lambda *s: torch.randn(*s, dtype=torch.bfloat16) * 1.6)(Hq * Dh, D) * ((Hq * Dh) ** -0.5)),
        }
    _A_in = _A_setup()

    def _B_setup():
        B, S, Dm, Df = 1, 1, 1024, 3584
        return {
            "x": _w((lambda *s: torch.randn(*s, dtype=torch.bfloat16) * 0.05)(B, S, Dm)),
            "w_gate": _w((lambda *s: torch.randn(*s, dtype=torch.bfloat16) * 1.6)(Dm, Df) * (Dm ** -0.5)),
            "w_up": _w((lambda *s: torch.randn(*s, dtype=torch.bfloat16) * 1.6)(Dm, Df) * (Dm ** -0.5)),
            "w_down": _w((lambda *s: torch.randn(*s, dtype=torch.bfloat16) * 1.6)(Df, Dm) * (Df ** -0.5)),
        }
    _B_in = _B_setup()

    return {
        "A_x": _A_in["x"],
        "A_k_cache": _A_in["k_cache"],
        "A_v_cache": _A_in["v_cache"],
        "A_wq": _A_in["wq"],
        "A_wo": _A_in["wo"],
        "B_x": _B_in["x"],
        "B_w_gate": _B_in["w_gate"],
        "B_w_up": _B_in["w_up"],
        "B_w_down": _B_in["w_down"],
    }

def reference(A_x, A_k_cache, A_v_cache, A_wq, A_wo, B_x, B_w_gate, B_w_up, B_w_down):
    def _A_ref(x, k_cache, v_cache, wq, wo):
        B, Sq, D = x.shape
        Hq, Dh = 32, 128
        Hkv = k_cache.shape[1]
        rep = Hq // Hkv
        q = (lambda x, *d: x.permute(*d))((x @ wq).reshape(B, Sq, Hq, Dh), 0, 2, 1, 3)
        k = (lambda x, n, axis: torch.repeat_interleave(x, n, dim=axis))(k_cache, rep, axis=1)
        v = (lambda x, n, axis: torch.repeat_interleave(x, n, dim=axis))(v_cache, rep, axis=1)
        scores = torch.einsum("bhqd,bhkd->bhqk", q, k) * (Dh ** -0.5)
        p = _softmax(scores, axis=-1)
        o = torch.einsum("bhqk,bhkd->bhqd", p, v)
        return (lambda x, *d: x.permute(*d))(o, 0, 2, 1, 3).reshape(B, Sq, Hq * Dh) @ wo

    def _B_ref(x, w_gate, w_up, w_down):
        g = torch.einsum("bsd,df->bsf", x, w_gate)
        u = torch.einsum("bsd,df->bsf", x, w_up)
        h = _gelu(g) * u
        return torch.einsum("bsf,fd->bsd", h, w_down)

    x = A_x
    xn = _layernorm(x, axis=-1)
    return x + _A_ref(xn, A_k_cache, A_v_cache, A_wq, A_wo) + _B_ref(xn, B_w_gate, B_w_up, B_w_down)
```

```cpp
#include <cuda_runtime.h>
#include <cuda_bf16.h>
#include <cuda.h>
#include <stdint.h>

namespace {

constexpr int D_MODEL = 1024;
constexpr int N_HKV = 4;
constexpr int S_K = 65536;
constexpr int D_FF = 3584;
constexpr int QCOLS = 4096;

constexpr int NCTA = 128;
constexpr int CPG = 32;
constexpr int TILE_KEYS = 64;
constexpr int KV_TILES = S_K / CPG / TILE_KEYS;
constexpr int KV0 = 2;
constexpr int GU0 = KV0 + KV_TILES;
constexpr int WO0 = GU0 + 4;
constexpr int DN0 = WO0 + 2;
constexpr int N_STEPS = DN0 + 2;
constexpr int STAGES = 4;
#define WIN 3
#define WIN_TAIL WIN
#define TAIL0 WO0
#define WIN_HEAD 4
#define KV_PROMO CU_TENSOR_MAP_L2_PROMOTION_L2_256B
#define DELAY_O 0
#define PROBE_NS 300
#define V_PROBE 6
#define POLL_NS 1500
constexpr int HALF_BYTES = 16384;
constexpr int STAGE_BYTES = 2 * HALF_BYTES;
constexpr int SMALL_BYTES = 14336;
constexpr int RG = 8;
constexpr int FF_G = D_FF / (NCTA / RG);
constexpr int NTHREADS = 320;

constexpr int MRG_HS = 132;
constexpr int MRG_WS = 8 * MRG_HS;

constexpr int OFF_MRG = STAGES * STAGE_BYTES;
constexpr int OFF_XN = OFF_MRG + 8 * MRG_WS * 4;
constexpr int OFF_XB = OFF_XN + 4096;
constexpr int OFF_Q = OFF_XB + 2048;
constexpr int OFF_REDQ = OFF_Q + 2048;
constexpr int OFF_REDG = OFF_REDQ + 1024;
constexpr int OFF_MS = OFF_REDG + 4 * 448 * 4;
constexpr int OFF_LS = OFF_MS + 256;
constexpr int OFF_LN = OFF_LS + 256;
constexpr int OFF_VEC = OFF_LN + 64;
constexpr int OFF_BAR = OFF_VEC + 1024;
constexpr int N_BARS = 3 * STAGES + 2;
constexpr int SMEM_USED = OFF_BAR + N_BARS * 8;
constexpr int SMEM_BYTES = SMEM_USED + 1024;

constexpr int P_REC = 40;
constexpr int BOX_O = CPG * P_REC;
constexpr int BOX_WORDS = BOX_O + 16 * 8;
constexpr int OUT_O = 2 * FF_G;
constexpr int OUT_WORDS = OUT_O + 32;
constexpr uint32_t TAG_MASK = 15u;
constexpr unsigned SPIN_LIMIT = 1u << 22;

constexpr float LOG2E = 1.4426950408889634f;
constexpr float SM_SCALE = 0.08838834764831845f;

__device__ unsigned int g_epoch;
__device__ __align__(128) unsigned long long g_qbox[QCOLS / 2];
__device__ __align__(128) uint32_t g_inbox[NCTA * BOX_WORDS];
__device__ __align__(128) uint32_t g_outbox[NCTA * OUT_WORDS];
#define PROF(i) do { } while (0)
#define LAND(i) do { } while (0)

__device__ __forceinline__ uint32_t smem_u32(const void* p) { return (uint32_t)__cvta_generic_to_shared(p); }
__device__ __forceinline__ void mbar_init(uint32_t a, uint32_t c) {
    asm volatile("mbarrier.init.shared::cta.b64 [%0], %1;" ::"r"(a), "r"(c) : "memory");
}
__device__ __forceinline__ void mbar_expect_tx(uint32_t a, uint32_t bytes) {
    asm volatile("mbarrier.arrive.expect_tx.shared::cta.b64 _, [%0], %1;" ::"r"(a), "r"(bytes) : "memory");
}
__device__ __forceinline__ void mbar_arrive(uint32_t a) {
    asm volatile("mbarrier.arrive.shared::cta.b64 _, [%0];" ::"r"(a) : "memory");
}
__device__ __forceinline__ bool mbar_try(uint32_t a, uint32_t parity) {
    uint32_t ok;
    asm volatile("{\n.reg .pred p;\nmbarrier.try_wait.parity.shared::cta.b64 p, [%1], %2;\nselp.u32 %0, 1, 0, p;\n}"
                 : "=r"(ok) : "r"(a), "r"(parity) : "memory");
    return ok != 0;
}
__device__ __forceinline__ bool mbar_try_ns(uint32_t a, uint32_t parity, uint32_t ns) {
    uint32_t ok;
    asm volatile("{\n.reg .pred p;\nmbarrier.try_wait.parity.shared::cta.b64 p, [%1], %2, %3;\nselp.u32 %0, 1, 0, p;\n}"
                 : "=r"(ok) : "r"(a), "r"(parity), "r"(ns) : "memory");
    return ok != 0;
}
__device__ __forceinline__ void mbar_wait(uint32_t a, uint32_t parity) {
    unsigned n = 0;
    while (!mbar_try(a, parity)) {
        if (++n > SPIN_LIMIT) __trap();
    }
}
__device__ __forceinline__ void tma2d(uint32_t dst, const CUtensorMap* tm, int c0, int c1, uint32_t bar, uint64_t pol) {
    asm volatile("cp.async.bulk.tensor.2d.shared::cluster.global.mbarrier::complete_tx::bytes.L2::cache_hint [%0], [%1, {%3, %4}], [%2], %5;"
                 ::"r"(dst), "l"(tm), "r"(bar), "r"(c0), "r"(c1), "l"(pol) : "memory");
}
__device__ __forceinline__ void tma3d(uint32_t dst, const CUtensorMap* tm, int c0, int c1, int c2, uint32_t bar, uint64_t pol) {
    asm volatile("cp.async.bulk.tensor.3d.shared::cluster.global.mbarrier::complete_tx::bytes.L2::cache_hint [%0], [%1, {%3, %4, %5}], [%2], %6;"
                 ::"r"(dst), "l"(tm), "r"(bar), "r"(c0), "r"(c1), "r"(c2), "l"(pol) : "memory");
}
__device__ __forceinline__ void prefetch_tmap(const CUtensorMap* tm) {
    asm volatile("prefetch.tensormap [%0];" ::"l"(tm) : "memory");
}
__device__ __forceinline__ void prefetch_l2(const void* p, uint32_t bytes) {
    asm volatile("cp.async.bulk.prefetch.L2.global [%0], %1;" ::"l"(p), "r"(bytes) : "memory");
}
__device__ __forceinline__ void cons_sync() { asm volatile("bar.sync 1, 256;" ::: "memory"); }

__device__ __forceinline__ uint4 lds128(uint32_t a) {
    uint4 v;
    asm volatile("ld.shared.v4.u32 {%0, %1, %2, %3}, [%4];" : "=r"(v.x), "=r"(v.y), "=r"(v.z), "=r"(v.w) : "r"(a));
    return v;
}
__device__ __forceinline__ void ldsm4(uint32_t a, uint32_t& r0, uint32_t& r1, uint32_t& r2, uint32_t& r3) {
    asm volatile("ldmatrix.sync.aligned.m8n8.x4.shared.b16 {%0, %1, %2, %3}, [%4];"
                 : "=r"(r0), "=r"(r1), "=r"(r2), "=r"(r3) : "r"(a));
}
__device__ __forceinline__ void ldsm4t(uint32_t a, uint32_t& r0, uint32_t& r1, uint32_t& r2, uint32_t& r3) {
    asm volatile("ldmatrix.sync.aligned.m8n8.x4.trans.shared.b16 {%0, %1, %2, %3}, [%4];"
                 : "=r"(r0), "=r"(r1), "=r"(r2), "=r"(r3) : "r"(a));
}
__device__ __forceinline__ void mma16816(float (&c)[4], uint32_t a0, uint32_t a1, uint32_t a2, uint32_t a3,
                                         uint32_t b0, uint32_t b1) {
    asm volatile("mma.sync.aligned.m16n8k16.row.col.f32.bf16.bf16.f32 {%0, %1, %2, %3}, {%4, %5, %6, %7}, {%8, %9}, {%0, %1, %2, %3};"
                 : "+f"(c[0]), "+f"(c[1]), "+f"(c[2]), "+f"(c[3])
                 : "r"(a0), "r"(a1), "r"(a2), "r"(a3), "r"(b0), "r"(b1));
}
__device__ __forceinline__ uint32_t movm_t(uint32_t a) {
    uint32_t d;
    asm volatile("movmatrix.sync.aligned.m8n8.trans.b16 %0, %1;" : "=r"(d) : "r"(a));
    return d;
}
__device__ __forceinline__ uint32_t pack_bf16(float lo, float hi) {
    uint32_t r;
    asm("cvt.rn.bf16x2.f32 %0, %1, %2;" : "=r"(r) : "f"(hi), "f"(lo));
    return r;
}
__device__ __forceinline__ float bf_lo(uint32_t v) { return __uint_as_float(v << 16); }
__device__ __forceinline__ float bf_hi(uint32_t v) { return __uint_as_float(v & 0xffff0000u); }
__device__ __forceinline__ float rbf(float x) { return __bfloat162float(__float2bfloat16_rn(x)); }
__device__ __forceinline__ float ex2(float x) {
    float y;
    asm("ex2.approx.ftz.f32 %0, %1;" : "=f"(y) : "f"(x));
    return y;
}
__device__ __forceinline__ void box_st1(unsigned long long* p, uint32_t payload, uint32_t epoch) {
    asm volatile("st.relaxed.gpu.global.b64 [%0], %1;" ::"l"(p), "l"(((unsigned long long)epoch << 32) | payload) : "memory");
}
__device__ __forceinline__ void box_ld2(const unsigned long long* p, unsigned long long& a, unsigned long long& b) {
    asm volatile("ld.relaxed.gpu.global.v2.b64 {%0, %1}, [%2];" : "=l"(a), "=l"(b) : "l"(p) : "memory");
}
__device__ __forceinline__ uint32_t pay(float v, uint32_t tag) { return (__float_as_uint(v) & ~TAG_MASK) | tag; }
__device__ __forceinline__ float val(uint32_t w) { return __uint_as_float(w & ~TAG_MASK); }
__device__ __forceinline__ bool tagged4(const uint4& v, uint32_t tag) {
    return (((v.x ^ tag) | (v.y ^ tag) | (v.z ^ tag) | (v.w ^ tag)) & TAG_MASK) == 0;
}
__device__ __forceinline__ void in_st1(uint32_t* p, uint32_t a) {
    asm volatile("st.relaxed.gpu.global.b32 [%0], %1;" ::"l"(p), "r"(a) : "memory");
}
__device__ __forceinline__ void in_st4(uint32_t* p, uint32_t a, uint32_t b, uint32_t c, uint32_t d) {
    asm volatile("st.relaxed.gpu.global.v4.b32 [%0], {%1, %2, %3, %4};" ::"l"(p), "r"(a), "r"(b), "r"(c), "r"(d) : "memory");
}
__device__ __forceinline__ uint4 in_ld4(const uint32_t* p) {
    uint4 v;
    asm volatile("ld.relaxed.gpu.global.v4.b32 {%0, %1, %2, %3}, [%4];" : "=r"(v.x), "=r"(v.y), "=r"(v.z), "=r"(v.w) : "l"(p) : "memory");
    return v;
}
__device__ __forceinline__ uint32_t in_ld1(const uint32_t* p) {
    uint32_t v;
    asm volatile("ld.relaxed.gpu.global.b32 %0, [%1];" : "=r"(v) : "l"(p) : "memory");
    return v;
}
__device__ __forceinline__ uint32_t ld_epoch() {
    uint32_t e;
    asm volatile("ld.relaxed.gpu.global.u32 %0, [%1];" : "=r"(e) : "l"(&g_epoch) : "memory");
    return e + 1;
}

__device__ __forceinline__ void fma8(float (&acc)[8], const uint4& w, float x) {
    acc[0] = fmaf(x, bf_lo(w.x), acc[0]); acc[1] = fmaf(x, bf_hi(w.x), acc[1]);
    acc[2] = fmaf(x, bf_lo(w.y), acc[2]); acc[3] = fmaf(x, bf_hi(w.y), acc[3]);
    acc[4] = fmaf(x, bf_lo(w.z), acc[4]); acc[5] = fmaf(x, bf_hi(w.z), acc[5]);
    acc[6] = fmaf(x, bf_lo(w.w), acc[6]); acc[7] = fmaf(x, bf_hi(w.w), acc[7]);
}
__device__ __forceinline__ void red_quads(float (&acc)[8]) {
#pragma unroll
    for (int i = 0; i < 8; i++) {
        acc[i] += __shfl_xor_sync(0xffffffffu, acc[i], 4);
        acc[i] += __shfl_xor_sync(0xffffffffu, acc[i], 8);
        acc[i] += __shfl_xor_sync(0xffffffffu, acc[i], 16);
    }
}
__device__ __forceinline__ float warp_sum(float v) {
#pragma unroll
    for (int o = 16; o > 0; o >>= 1) v += __shfl_xor_sync(0xffffffffu, v, o);
    return v;
}

template <int W>
__device__ __forceinline__ void fold(float (&v)[32], int lane) {
    const bool up = lane & W;
#pragma unroll
    for (int i = 0; i < W; i++) {
        const float keep = up ? v[W + i] : v[i], send = up ? v[i] : v[W + i];
        v[i] = keep + __shfl_xor_sync(0xffffffffu, send, W);
    }
}

template <int G>
__device__ __forceinline__ void rows_step(uint32_t stage, const uint32_t* vec, int warp, int lane, float (&c0)[4], float (&c1)[4]) {
    const int mi = lane >> 3, r7 = lane & 7, t = lane & 3;
    const uint32_t base = stage + (warp >> 2) * (G * 1024) + r7 * 128 + (((2 * (warp & 3) + (mi & 1)) ^ r7) << 4);
#pragma unroll
    for (int ks = 0; ks < G; ks++) {
        const int gi = 2 * ks + (mi >> 1);
        uint32_t a0, a1, a2, a3;
        ldsm4t(base + (gi >= G ? HALF_BYTES + (gi - G) * 1024 : gi * 1024), a0, a1, a2, a3);
        if (ks & 1) mma16816(c1, a0, a1, a2, a3, vec[8 * ks + t], vec[8 * ks + 4 + t]);
        else mma16816(c0, a0, a1, a2, a3, vec[8 * ks + t], vec[8 * ks + 4 + t]);
    }
}

struct Maps { CUtensorMap k, v, q, g, u, d, o; };

__global__ void __launch_bounds__(NTHREADS, 1)
fused_decode_kernel(const __grid_constant__ Maps tm, const __nv_bfloat16* __restrict__ x,
                    const __nv_bfloat16* __restrict__ kc, const __nv_bfloat16* __restrict__ vc,
                    __nv_bfloat16* __restrict__ out) {
    extern __shared__ unsigned char smem_raw[];
    unsigned char* smem = smem_raw + ((1024u - (smem_u32(smem_raw) & 1023u)) & 1023u);
    const uint32_t sbase = smem_u32(smem);
    const uint32_t bar_fullA = sbase + OFF_BAR;
    const uint32_t bar_fullB = bar_fullA + 8 * STAGES;
    const uint32_t bar_empty = bar_fullB + 8 * STAGES;
    const uint32_t bar_kv = bar_empty + 8 * STAGES;
    const uint32_t bar_pub = bar_kv + 8;

    const int tid = threadIdx.x, warp = tid >> 5, lane = tid & 31;
    const int cta = blockIdx.x, grp = cta / CPG, gj = cta % CPG;
    const int rho = cta / RG, kap = cta % RG;
    uint32_t* const inbox = &g_inbox[cta * BOX_WORDS];

    if (warp == 8) {
        const int key0 = grp * S_K + gj * TILE_KEYS;
        uint64_t pol, pol_q;
        asm volatile("createpolicy.fractional.L2::evict_first.b64 %0, 1.0;" : "=l"(pol));
        asm volatile("createpolicy.fractional.L2::evict_normal.b64 %0, 1.0;" : "=l"(pol_q));
        auto issue = [&](int v) {
            const int n = v >> 1, hb = v & 1, s = n % STAGES;
            const uint32_t dst = sbase + s * STAGE_BYTES + hb * HALF_BYTES;
            const uint32_t bar = (hb ? bar_fullB : bar_fullA) + 8 * s;
            mbar_expect_tx(bar, ((n >= GU0 && n < WO0) || n >= DN0) ? SMALL_BYTES : HALF_BYTES);
            if (n < KV0) tma2d(dst, &tm.q, cta * 32, v * 256, bar, pol_q);
            else if (n < GU0) tma3d(dst, hb ? &tm.v : &tm.k, 0, key0 + (n - KV0) * (CPG * TILE_KEYS), 0, bar, pol);
            else if (n < WO0) tma2d(dst, hb ? &tm.u : &tm.g, rho * FF_G, kap * 128 + (n - GU0) * 32, bar, pol);
            else if (n < DN0) tma3d(dst, &tm.o, 0, rho * 256 + (v - 2 * WO0) * 64, 2 * kap, bar, pol);
            else tma3d(dst, &tm.d, 0, rho * FF_G + (v - 2 * DN0) * 56, 2 * kap, bar, pol);
        };
        if (lane == 0) {
            PROF(0);
#pragma unroll
            for (int s = 0; s < STAGES; s++) {
                mbar_init(bar_fullA + 8 * s, 1);
                mbar_init(bar_fullB + 8 * s, 1);
                mbar_init(bar_empty + 8 * s, 4);
            }
            mbar_init(bar_kv, 9);
            mbar_init(bar_pub, 8);
            asm volatile("fence.mbarrier_init.release.cluster;" ::: "memory");
            asm volatile("fence.proxy.async.shared::cta;" ::: "memory");
#pragma unroll
            for (int v = 0; v < WIN_HEAD; v++) issue(v);
        } else if (lane < 7) {
            prefetch_tmap(&tm.k + (lane == 1 ? 0 : lane == 2 ? 1 : lane));
        }
        __syncthreads();
        if (lane == 0) {
            for (int v = WIN_HEAD; v < 2 * N_STEPS; v++) {
                const int n = v >> 1, w = v - (n >= TAIL0 ? WIN_TAIL : WIN), wn = w >> 1;
                mbar_wait(((w & 1) ? bar_fullB : bar_fullA) + 8 * (wn % STAGES), (wn / STAGES) & 1);
                LAND(w);
                if (!(v & 1) && n >= STAGES) mbar_wait(bar_empty + 8 * (n % STAGES), ((n / STAGES) & 1) ^ 1);
                issue(v);
                if (v == 2 * GU0 - 1) PROF(1);
                if (v == 2 * GU0 + V_PROBE) mbar_arrive(bar_kv);
            }
            PROF(12);
        }
        return;
    }

    if (warp == 9) {
        const uint32_t epoch = ld_epoch(), tag = epoch & TAG_MASK;
        const int ocol = kap * 128 + rho * 8 + (lane >> 2);
        const float xres = __bfloat162float(x[ocol]);
        __syncthreads();
        unsigned n = 0;
        mbar_wait(bar_kv, 0);
        {
            const uint32_t* src = inbox + lane * P_REC;
            uint4 a[8], ml;
            while (true) {
                ml = in_ld4(src + 32);
                if (tagged4(ml, tag)) break;
                if (++n > SPIN_LIMIT) __trap();
                __nanosleep(PROBE_NS);
            }
            while (true) {
#pragma unroll
                for (int i = 0; i < 8; i++) a[i] = in_ld4(src + 4 * i);
                bool ok = true;
#pragma unroll
                for (int i = 0; i < 8; i++) ok = ok && tagged4(a[i], tag);
                if (ok) break;
                if (++n > SPIN_LIMIT) __trap();
                __nanosleep(300);
            }
            __syncwarp();
            const float m = val(ml.x);
            int key = __float_as_int(m);
            key = key >= 0 ? key : key ^ 0x7fffffff;
            key = __reduce_max_sync(0xffffffffu, key);
            key = key >= 0 ? key : key ^ 0x7fffffff;
            const float wgt = ex2((m - __int_as_float(key)) * LOG2E);
            const float L = warp_sum(val(ml.y) * wgt);
            float v[32];
#pragma unroll
            for (int i = 0; i < 8; i++) {
                v[4 * i] = val(a[i].x) * wgt; v[4 * i + 1] = val(a[i].y) * wgt;
                v[4 * i + 2] = val(a[i].z) * wgt; v[4 * i + 3] = val(a[i].w) * wgt;
            }
            fold<16>(v, lane); fold<8>(v, lane); fold<4>(v, lane); fold<2>(v, lane); fold<1>(v, lane);
            const uint32_t ob = pack_bf16(0.f, __fdiv_rn(v[0], L));
            in_st1(&g_outbox[cta * OUT_WORDS + OUT_O + lane], ob | tag);
            if (lane == 0) PROF(8);
        }
        const uint32_t* src = inbox + BOX_O + lane * 4;
        uint4 a;
        bool own_done = false;
        while (true) {
            a = in_ld4(src);
            if (tagged4(a, tag)) break;
            if (++n > SPIN_LIMIT) __trap();
            if (!own_done) own_done = mbar_try_ns(bar_pub, 0, POLL_NS);
        }
        __syncwarp();
        const bool b4 = lane & 16, b3 = lane & 8;
        float v0 = (b4 ? val(a.z) : val(a.x)) + __shfl_xor_sync(0xffffffffu, b4 ? val(a.x) : val(a.z), 16);
        float v1 = (b4 ? val(a.w) : val(a.y)) + __shfl_xor_sync(0xffffffffu, b4 ? val(a.y) : val(a.w), 16);
        float r = (b3 ? v1 : v0) + __shfl_xor_sync(0xffffffffu, b3 ? v0 : v1, 8);
        r += __shfl_xor_sync(0xffffffffu, r, 4);
        r += __shfl_xor_sync(0xffffffffu, r, 2);
        const int c = lane >> 2;
        r = __shfl_sync(0xffffffffu, r, (c >> 2) | ((c & 2) << 3) | ((c & 1) << 3));
        if ((lane & 3) == 0) out[ocol] = __float2bfloat16_rn(xres + r);
        if (cta == 0 && lane == 0) g_epoch = epoch;
        if (lane == 0) PROF(11);
        return;
    }

    float* xn = reinterpret_cast<float*>(smem + OFF_XN);
    const int g = lane >> 2, t = lane & 3;
    uint2 xraw;
    asm volatile("ld.global.nc.v2.u32 {%0, %1}, [%2];" : "=r"(xraw.x), "=r"(xraw.y) : "l"(x + tid * 4));
    const uint32_t epoch = ld_epoch(), tag = epoch & TAG_MASK;
    {
        float* ln = reinterpret_cast<float*>(smem + OFF_LN);
        const float x0 = bf_lo(xraw.x), x1 = bf_hi(xraw.x), x2 = bf_lo(xraw.y), x3 = bf_hi(xraw.y);
        float s = warp_sum((x0 + x1) + (x2 + x3));
        if (lane == 0) ln[warp] = s;
        __syncthreads();
        float tot = 0.f;
#pragma unroll
        for (int i = 0; i < 8; i++) tot += ln[i];
        const float mean = tot * (1.0f / D_MODEL);
        const float d0 = x0 - mean, d1 = x1 - mean, d2 = x2 - mean, d3 = x3 - mean;
        float v = warp_sum((d0 * d0 + d1 * d1) + (d2 * d2 + d3 * d3));
        if (lane == 0) ln[8 + warp] = v;
        cons_sync();
        float vt = 0.f;
#pragma unroll
        for (int i = 0; i < 8; i++) vt += ln[8 + i];
        const float mb = rbf(mean);
        const float sd = rbf(__fsqrt_rn(rbf(rbf(vt * (1.0f / D_MODEL)) + 1e-5f)));
        float4 o;
        o.x = rbf(__fdiv_rn(rbf(x0 - mb), sd));
        o.y = rbf(__fdiv_rn(rbf(x1 - mb), sd));
        o.z = rbf(__fdiv_rn(rbf(x2 - mb), sd));
        o.w = rbf(__fdiv_rn(rbf(x3 - mb), sd));
        reinterpret_cast<float4*>(xn)[tid] = o;
        reinterpret_cast<uint2*>(smem + OFF_XB)[tid] = make_uint2(pack_bf16(o.x, o.y), pack_bf16(o.z, o.w));
        cons_sync();
    }
    if (tid == 0) PROF(2);
    const int half = warp >> 2;
    const int gt = tid & 127;
    uint32_t qf[8][2];
    {
        float acc[8] = {0.f, 0.f, 0.f, 0.f, 0.f, 0.f, 0.f, 0.f};
        const uint32_t a = sbase + half * STAGE_BYTES + gt * 16;
        const float* xr = xn + half * 512 + (gt >> 2);
        mbar_wait(bar_fullA + 8 * half, 0);
#pragma unroll
        for (int i = 0; i < 8; i++) fma8(acc, lds128(a + i * 2048), xr[32 * i]);
        mbar_wait(bar_fullB + 8 * half, 0);
#pragma unroll
        for (int i = 0; i < 8; i++) fma8(acc, lds128(a + HALF_BYTES + i * 2048), xr[256 + 32 * i]);
        __syncwarp();
        if (lane == 0) mbar_arrive(bar_empty + 8 * half);
        red_quads(acc);
        float* rq = reinterpret_cast<float*>(smem + OFF_REDQ);
        if (lane < 4) {
            reinterpret_cast<float4*>(rq + warp * 32 + lane * 8)[0] = make_float4(acc[0], acc[1], acc[2], acc[3]);
            reinterpret_cast<float4*>(rq + warp * 32 + lane * 8)[1] = make_float4(acc[4], acc[5], acc[6], acc[7]);
        }
        cons_sync();
        if (tid < 16) {
            float qa = 0.f, qb = 0.f;
#pragma unroll
            for (int w = 0; w < 8; w++) { qa += rq[w * 32 + 2 * tid]; qb += rq[w * 32 + 2 * tid + 1]; }
            box_st1(&g_qbox[cta * 16 + tid], pack_bf16(qa, qb), epoch);
        }
        if (tid == 0) PROF(3);
        const unsigned long long* src = &g_qbox[grp * 512 + 2 * tid];
        unsigned long long qa, qb;
        unsigned n = 0;
        while (true) {
            box_ld2(src, qa, qb);
            if ((uint32_t)(qa >> 32) == epoch && (uint32_t)(qb >> 32) == epoch) break;
            if (++n > SPIN_LIMIT) __trap();
            __nanosleep(100);
        }
        uint32_t* qs = reinterpret_cast<uint32_t*>(smem + OFF_Q);
        reinterpret_cast<uint2*>(qs)[tid] = make_uint2((uint32_t)qa, (uint32_t)qb);
        cons_sync();
#pragma unroll
        for (int ks = 0; ks < 8; ks++) {
            qf[ks][0] = qs[g * 64 + ks * 8 + t];
            qf[ks][1] = qs[g * 64 + ks * 8 + 4 + t];
        }
    }
    if (tid == 0) PROF(5);

    {
        float o[8][4];
#pragma unroll
        for (int i = 0; i < 8; i++) o[i][0] = o[i][1] = o[i][2] = o[i][3] = 0.f;
        float m0 = -INFINITY, m1 = -INFINITY, l0 = 0.f, l1 = 0.f;
        const int kw = (warp & 3) * 16, r7 = lane & 7, mi = lane >> 3;
        const uint32_t k_row = (kw + r7 + 8 * (mi & 1)) * 128;
        const uint32_t v_row = HALF_BYTES + (kw + r7 + 8 * (mi >> 1)) * 128;
        uint32_t k_off[4], v_off[4];
#pragma unroll
        for (int j = 0; j < 4; j++) {
            k_off[j] = k_row + (((2 * j + (mi >> 1)) ^ r7) << 4);
            v_off[j] = v_row + (((2 * j + (mi & 1)) ^ r7) << 4);
        }
        for (int n = KV0 + half; n < GU0; n += 2) {
            const int s = n % STAGES;
            const uint32_t ph = (n / STAGES) & 1;
            const uint32_t base = sbase + s * STAGE_BYTES;
            float sa[4] = {0.f, 0.f, 0.f, 0.f}, sb[4] = {0.f, 0.f, 0.f, 0.f};
            mbar_wait(bar_fullA + 8 * s, ph);
#pragma unroll
            for (int j = 0; j < 4; j++) {
                uint32_t a0, a1, a2, a3, c0, c1, c2, c3;
                ldsm4(base + k_off[j], a0, a1, a2, a3);
                ldsm4(base + k_off[j] + 8192, c0, c1, c2, c3);
                mma16816(sa, a0, a1, a2, a3, qf[j][0], qf[j][1]);
                mma16816(sb, c0, c1, c2, c3, qf[4 + j][0], qf[4 + j][1]);
            }
            const uint32_t r01 = pack_bf16(sa[0] + sb[0], sa[1] + sb[1]);
            const uint32_t r23 = pack_bf16(sa[2] + sb[2], sa[3] + sb[3]);
            const uint32_t u01 = pack_bf16(bf_lo(r01) * SM_SCALE, bf_hi(r01) * SM_SCALE);
            const uint32_t u23 = pack_bf16(bf_lo(r23) * SM_SCALE, bf_hi(r23) * SM_SCALE);
            const float s0 = bf_lo(u01), s1 = bf_hi(u01), s2 = bf_lo(u23), s3 = bf_hi(u23);
            float t0 = fmaxf(s0, s2), t1 = fmaxf(s1, s3);
#pragma unroll
            for (int sh = 4; sh <= 16; sh <<= 1) {
                t0 = fmaxf(t0, __shfl_xor_sync(0xffffffffu, t0, sh));
                t1 = fmaxf(t1, __shfl_xor_sync(0xffffffffu, t1, sh));
            }
            if (__any_sync(0xffffffffu, t0 > m0 || t1 > m1)) {
                const float n0 = fmaxf(m0, t0), n1 = fmaxf(m1, t1);
                const float f0 = ex2((m0 - n0) * LOG2E), f1 = ex2((m1 - n1) * LOG2E);
                m0 = n0; m1 = n1;
                l0 *= f0; l1 *= f1;
#pragma unroll
                for (int i = 0; i < 8; i++) { o[i][0] *= f0; o[i][1] *= f1; o[i][2] *= f0; o[i][3] *= f1; }
            }
            const float p0 = ex2((s0 - m0) * LOG2E), p1 = ex2((s1 - m1) * LOG2E);
            const float p2 = ex2((s2 - m0) * LOG2E), p3 = ex2((s3 - m1) * LOG2E);
            l0 += p0 + p2;
            l1 += p1 + p3;
            const uint32_t b0 = movm_t(pack_bf16(p0, p1));
            const uint32_t b1 = movm_t(pack_bf16(p2, p3));
            mbar_wait(bar_fullB + 8 * s, ph);
#pragma unroll
            for (int j = 0; j < 4; j++) {
                uint32_t a0, a1, a2, a3, c0, c1, c2, c3;
                ldsm4t(base + v_off[j], a0, a1, a2, a3);
                ldsm4t(base + v_off[j] + 8192, c0, c1, c2, c3);
                mma16816(o[j], a0, a1, a2, a3, b0, b1);
                mma16816(o[4 + j], c0, c1, c2, c3, b0, b1);
            }
            __syncwarp();
            if (lane == 0) mbar_arrive(bar_empty + 8 * s);
        }
        if (tid == 0) PROF(6);

        float* ms = reinterpret_cast<float*>(smem + OFF_MS);
        float* ls = reinterpret_cast<float*>(smem + OFF_LS);
        float* mrg = reinterpret_cast<float*>(smem + OFF_MRG);
        if (g == 0) reinterpret_cast<float2*>(ms + warp * 8)[t] = make_float2(m0, m1);
#pragma unroll
        for (int sh = 4; sh <= 16; sh <<= 1) {
            l0 += __shfl_xor_sync(0xffffffffu, l0, sh);
            l1 += __shfl_xor_sync(0xffffffffu, l1, sh);
        }
        cons_sync();
        float M0 = -INFINITY, M1 = -INFINITY;
#pragma unroll
        for (int w = 0; w < 8; w++) {
            const float2 v = reinterpret_cast<const float2*>(ms + w * 8)[t];
            M0 = fmaxf(M0, v.x); M1 = fmaxf(M1, v.y);
        }
        const float f0 = ex2((m0 - M0) * LOG2E), f1 = ex2((m1 - M1) * LOG2E);
        if (g == 0) reinterpret_cast<float2*>(ls + warp * 8)[t] = make_float2(l0 * f0, l1 * f1);
        float* dst = mrg + warp * MRG_WS + 2 * t * MRG_HS + g;
#pragma unroll
        for (int i = 0; i < 8; i++) {
            dst[16 * i] = o[i][0] * f0;
            dst[16 * i + MRG_HS] = o[i][1] * f1;
            dst[16 * i + 8] = o[i][2] * f0;
            dst[16 * i + 8 + MRG_HS] = o[i][3] * f1;
        }
        cons_sync();
        float a0 = 0.f, a1 = 0.f, a2 = 0.f, a3 = 0.f, L = 0.f, M = -INFINITY;
#pragma unroll
        for (int w = 0; w < 8; w++) {
            const float4 u = *reinterpret_cast<const float4*>(mrg + w * MRG_WS + warp * MRG_HS + 4 * lane);
            a0 += u.x; a1 += u.y; a2 += u.z; a3 += u.w;
            L += ls[w * 8 + warp];
            M = fmaxf(M, ms[w * 8 + warp]);
        }
        uint32_t* pb = &g_inbox[(grp * CPG + warp * 4) * BOX_WORDS + gj * P_REC];
        in_st4(pb + (lane >> 3) * BOX_WORDS + (lane & 7) * 4, pay(a0, tag), pay(a1, tag), pay(a2, tag), pay(a3, tag));
        if (lane < 8)
            in_st4(pb + (lane >> 1) * BOX_WORDS + 32 + (lane & 1) * 4, pay(M, tag), pay(L, tag), pay(M, tag), pay(L, tag));
        __syncwarp();
        if (lane == 0) mbar_arrive(bar_kv);
    }
    if (tid == 0) PROF(7);

    {
        float cg[7][4], cu[7][4];
#pragma unroll
        for (int i = 0; i < 7; i++) {
            cg[i][0] = cg[i][1] = cg[i][2] = cg[i][3] = 0.f;
            cu[i][0] = cu[i][1] = cu[i][2] = cu[i][3] = 0.f;
        }
        const int ks = warp & 1, mg = (warp >> 1) & 1, mi = lane >> 3;
        const uint32_t a_off = (ks * 16 + (lane & 7) + 8 * (mi >> 1)) * (FF_G * 2) + (mg * 14 + (mi & 1)) * 16;
        const uint32_t* xb = reinterpret_cast<const uint32_t*>(smem + OFF_XB) + kap * 64 + ks * 8 + t;
#pragma unroll
        for (int k = 0; k < 2; k++) {
            const int n = GU0 + 2 * k + half;
            const int s = n % STAGES;
            const uint32_t ph = (n / STAGES) & 1;
            const uint32_t a = sbase + s * STAGE_BYTES + a_off;
            const uint32_t b0 = xb[(n - GU0) * 16], b1 = xb[(n - GU0) * 16 + 4];
            mbar_wait(bar_fullA + 8 * s, ph);
#pragma unroll
            for (int i = 0; i < 7; i++) {
                uint32_t a0, a1, a2, a3;
                ldsm4t(a + i * 32, a0, a1, a2, a3);
                mma16816(cg[i], a0, a1, a2, a3, b0, b1);
            }
            mbar_wait(bar_fullB + 8 * s, ph);
#pragma unroll
            for (int i = 0; i < 7; i++) {
                uint32_t a0, a1, a2, a3;
                ldsm4t(a + HALF_BYTES + i * 32, a0, a1, a2, a3);
                mma16816(cu[i], a0, a1, a2, a3, b0, b1);
            }
            __syncwarp();
            if (lane == 0) mbar_arrive(bar_empty + 8 * s);
        }
        float* rg = reinterpret_cast<float*>(smem + OFF_REDG);
        if (t < 2) {
            float* dst = rg + (half * 2 + ks) * (2 * FF_G) + t * FF_G + mg * 112 + g;
#pragma unroll
            for (int i = 0; i < 7; i++) {
                dst[16 * i] = t ? cu[i][0] : cg[i][0];
                dst[16 * i + 8] = t ? cu[i][2] : cg[i][2];
            }
        }
        cons_sync();
        if (tid < 2 * FF_G / 4) {
            const float4* p = reinterpret_cast<const float4*>(rg) + tid;
            const float4 u0 = p[0], u1 = p[112], u2 = p[224], u3 = p[336];
            in_st4(&g_outbox[cta * OUT_WORDS + 4 * tid], pay((u0.x + u1.x) + (u2.x + u3.x), tag),
                   pay((u0.y + u1.y) + (u2.y + u3.y), tag), pay((u0.z + u1.z) + (u2.z + u3.z), tag),
                   pay((u0.w + u1.w) + (u2.w + u3.w), tag));
        }
    }
    if (tid == 0) PROF(4);

    {
        __nv_bfloat16* vec = reinterpret_cast<__nv_bfloat16*>(smem + OFF_VEC);
        const uint32_t* vec2 = reinterpret_cast<const uint32_t*>(smem + OFF_VEC);
        const uint32_t* ob = &g_outbox[rho * RG * OUT_WORDS];
        float c0[4] = {0.f, 0.f, 0.f, 0.f}, c1[4] = {0.f, 0.f, 0.f, 0.f};
        unsigned n = 0;
        {
            uint32_t w;
            while (true) {
                w = in_ld1(ob + (tid >> 5) * OUT_WORDS + OUT_O + lane);
                if ((w & TAG_MASK) == tag) break;
                if (++n > SPIN_LIMIT) __trap();
                __nanosleep(100);
            }
            reinterpret_cast<uint16_t*>(vec)[tid] = (uint16_t)(w >> 16);
        }
        if (tid < FF_G) {
            if (lane < RG) {
                while ((in_ld1(ob + lane * OUT_WORDS + OUT_O - 1) & TAG_MASK) != tag) {
                    if (++n > SPIN_LIMIT) __trap();
                    __nanosleep(PROBE_NS);
                }
            }
            __syncwarp();
            uint32_t gw[RG], uw[RG];
            while (true) {
                uint32_t bad = 0;
#pragma unroll
                for (int k = 0; k < RG; k++) {
                    gw[k] = in_ld1(ob + k * OUT_WORDS + tid);
                    uw[k] = in_ld1(ob + k * OUT_WORDS + FF_G + tid);
                }
#pragma unroll
                for (int k = 0; k < RG; k++) bad |= (gw[k] ^ tag) | (uw[k] ^ tag);
                if ((bad & TAG_MASK) == 0) break;
                if (++n > SPIN_LIMIT) __trap();
                __nanosleep(100);
            }
            float gsum = 0.f, usum = 0.f;
#pragma unroll
            for (int k = 0; k < RG; k++) { gsum += val(gw[k]); usum += val(uw[k]); }
            const float gb = rbf(gsum), ub = rbf(usum);
            const float inner = 0.7978845608028654f * (gb + 0.044715f * gb * gb * gb);
            const float ge = rbf(0.5f * gb * (1.0f + tanhf(inner)));
            vec[256 + tid] = __float2bfloat16_rn(ge * ub);
        }
        cons_sync();
        if (tid == 0) PROF(13);
#pragma unroll
        for (int k = 0; k < 4; k++) {
            const int st = WO0 + k, s = st % STAGES;
            const uint32_t ph = (st / STAGES) & 1;
            mbar_wait(bar_fullA + 8 * s, ph);
            mbar_wait(bar_fullB + 8 * s, ph);
            if (k == 3 && tid == 0) PROF(9);
            if (k < 2) rows_step<8>(sbase + s * STAGE_BYTES, vec2 + k * 64, warp, lane, c0, c1);
            else rows_step<7>(sbase + s * STAGE_BYTES, vec2 + 128 + (k - 2) * 56, warp, lane, c0, c1);
        }
        if (t < 2)
            in_st1(&g_inbox[((2 * warp + t) * RG + kap) * BOX_WORDS + BOX_O + rho * 8 + g],
                   pay(t ? c0[2] + c1[2] : c0[0] + c1[0], tag));
        __syncwarp();
        if (lane == 0) mbar_arrive(bar_pub);
    }
    if (tid == 0) PROF(10);
}

typedef CUresult (*EncodeFn)(CUtensorMap*, CUtensorMapDataType, cuuint32_t, void*, const cuuint64_t*, const cuuint64_t*,
                             const cuuint32_t*, const cuuint32_t*, CUtensorMapInterleave, CUtensorMapSwizzle,
                             CUtensorMapL2promotion, CUtensorMapFloatOOBfill);

void map_blocks(EncodeFn enc, CUtensorMap* m, void* p, uint64_t rows, uint32_t row_elems, uint32_t box_rows) {
    const cuuint64_t gd[3] = {64, rows, row_elems / 64};
    const cuuint64_t gs[2] = {(cuuint64_t)row_elems * 2, 128};
    const cuuint32_t bd[3] = {64, box_rows, 2};
    const cuuint32_t es[3] = {1, 1, 1};
    enc(m, CU_TENSOR_MAP_DATA_TYPE_BFLOAT16, 3, p, gd, gs, bd, es, CU_TENSOR_MAP_INTERLEAVE_NONE,
        CU_TENSOR_MAP_SWIZZLE_128B, KV_PROMO, CU_TENSOR_MAP_FLOAT_OOB_FILL_NONE);
}
void map_cols(EncodeFn enc, CUtensorMap* m, void* p, uint64_t cols, uint32_t box_cols, uint32_t box_rows) {
    const cuuint64_t gd[2] = {cols, D_MODEL};
    const cuuint64_t gs[1] = {cols * 2};
    const cuuint32_t bd[2] = {box_cols, box_rows};
    const cuuint32_t es[2] = {1, 1};
    enc(m, CU_TENSOR_MAP_DATA_TYPE_BFLOAT16, 2, p, gd, gs, bd, es, CU_TENSOR_MAP_INTERLEAVE_NONE,
        CU_TENSOR_MAP_SWIZZLE_NONE, CU_TENSOR_MAP_L2_PROMOTION_L2_128B, CU_TENSOR_MAP_FLOAT_OOB_FILL_NONE);
}

}

extern "C" void kernel_launch(void* const* d_in, const int* in_sizes, int n_in, void* d_out, int out_size) {
    (void)in_sizes; (void)n_in; (void)out_size;
    static EncodeFn encode = nullptr;
    if (!encode) {
        void* fn = nullptr;
        cudaDriverEntryPointQueryResult qr;
        cudaGetDriverEntryPoint("cuTensorMapEncodeTiled", &fn, cudaEnableDefault, &qr);
        encode = (EncodeFn)fn;
        cudaFuncSetAttribute(fused_decode_kernel, cudaFuncAttributeMaxDynamicSharedMemorySize, SMEM_BYTES);
    }
    Maps tm;
    map_blocks(encode, &tm.k, d_in[1], (uint64_t)N_HKV * S_K, 128, TILE_KEYS);
    map_blocks(encode, &tm.v, d_in[2], (uint64_t)N_HKV * S_K, 128, TILE_KEYS);
    map_cols(encode, &tm.q, d_in[3], QCOLS, 32, 256);
    map_cols(encode, &tm.g, d_in[6], D_FF, FF_G, 32);
    map_cols(encode, &tm.u, d_in[7], D_FF, FF_G, 32);
    map_blocks(encode, &tm.d, d_in[8], D_FF, D_MODEL, 56);
    map_blocks(encode, &tm.o, d_in[4], QCOLS, D_MODEL, 64);
    fused_decode_kernel<<<NCTA, NTHREADS, SMEM_BYTES, cudaStreamPerThread>>>(
        tm, (const __nv_bfloat16*)d_in[0], (const __nv_bfloat16*)d_in[1], (const __nv_bfloat16*)d_in[2],
        (__nv_bfloat16*)d_out);
}
```

```cpp
#include <cuda_runtime.h>
#include <cuda_bf16.h>
#include <cuda.h>
#include <stdint.h>

namespace {

constexpr int D_MODEL = 1024;
constexpr int N_HKV = 4;
constexpr int S_K = 65536;
constexpr int D_FF = 3584;
constexpr int QCOLS = 4096;

constexpr int NCTA = 128;
constexpr int CPG = 32;
constexpr int TILE_KEYS = 64;
constexpr int KV_TILES = S_K / CPG / TILE_KEYS;
constexpr int KV0 = 2;
constexpr int GU0 = KV0 + KV_TILES;
constexpr int WO0 = GU0 + 4;
constexpr int DN0 = WO0 + 2;
constexpr int N_STEPS = DN0 + 2;
constexpr int STAGES = 4;
#define WIN 3
#define WIN_TAIL WIN
#define TAIL0 WO0
#define KV_PROMO CU_TENSOR_MAP_L2_PROMOTION_L2_256B
#define DELAY_O 0
#define PROBE_NS 300
#define V_PROBE 6
#define DRY0 0
#define BAL_T 96
#define BAL_TL 32
#define TAILU 1000
#define GU_BUMP0 66
#define GU_BUMP1 74
#define BAL_UP 1
#define SPARSE0 81
#define SPARSE_STEP 4
#define CNT0 9
#define CNT1 81
#define GU_PROMO CU_TENSOR_MAP_L2_PROMOTION_L2_128B
#define GU_ROW(kap, j) ((kap) * 128 + (j) * 32)
#define POLL_NS 1500
constexpr int HALF_BYTES = 16384;
constexpr int STAGE_BYTES = 2 * HALF_BYTES;
constexpr int SMALL_BYTES = 14336;
constexpr int RG = 8;
constexpr int FF_G = D_FF / (NCTA / RG);
constexpr int NTHREADS = 320;

constexpr int MRG_HS = 132;
constexpr int MRG_WS = 8 * MRG_HS;

constexpr int OFF_MRG = STAGES * STAGE_BYTES;
constexpr int OFF_XN = OFF_MRG + 8 * MRG_WS * 4;
constexpr int OFF_XB = OFF_XN + 4096;
constexpr int OFF_Q = OFF_XB + 2048;
constexpr int OFF_REDQ = OFF_Q + 2048;
constexpr int OFF_REDG = OFF_REDQ + 1024;
constexpr int OFF_MS = OFF_REDG + 4 * 448 * 4;
constexpr int OFF_LS = OFF_MS + 256;
constexpr int OFF_LN = OFF_LS + 256;
constexpr int OFF_VEC = OFF_LN + 64;
constexpr int OFF_TAB = OFF_VEC + 1024;
constexpr int OFF_BAR = OFF_TAB + 2 * N_STEPS * 16;
constexpr int N_BARS = 3 * STAGES + 2;
constexpr int SMEM_USED = OFF_BAR + N_BARS * 8;
constexpr int SMEM_BYTES = SMEM_USED + 1024;

constexpr int P_REC = 40;
constexpr int BOX_O = CPG * P_REC;
constexpr int BOX_WORDS = BOX_O + 16 * 8;
constexpr int OUT_O = 2 * FF_G;
constexpr int OUT_WORDS = OUT_O + 32;
constexpr uint32_t TAG_MASK = 15u;
constexpr unsigned SPIN_LIMIT = 1u << 22;

constexpr float LOG2E = 1.4426950408889634f;
constexpr float SM_SCALE = 0.08838834764831845f;

__device__ unsigned int g_epoch;
__device__ __align__(128) unsigned int g_count;
__device__ __align__(128) unsigned long long g_qbox[QCOLS / 2];
__device__ __align__(128) uint32_t g_inbox[NCTA * BOX_WORDS];
__device__ __align__(128) uint32_t g_outbox[NCTA * OUT_WORDS];
#define PROF(i) do { } while (0)
#define LAND(i) do { } while (0)
#define GT(i) do { } while (0)

__device__ __forceinline__ uint32_t smem_u32(const void* p) { return (uint32_t)__cvta_generic_to_shared(p); }
__device__ __forceinline__ void mbar_init(uint32_t a, uint32_t c) {
    asm volatile("mbarrier.init.shared::cta.b64 [%0], %1;" ::"r"(a), "r"(c) : "memory");
}
__device__ __forceinline__ void mbar_expect_tx(uint32_t a, uint32_t bytes) {
    asm volatile("mbarrier.arrive.expect_tx.shared::cta.b64 _, [%0], %1;" ::"r"(a), "r"(bytes) : "memory");
}
__device__ __forceinline__ void mbar_arrive(uint32_t a) {
    asm volatile("mbarrier.arrive.shared::cta.b64 _, [%0];" ::"r"(a) : "memory");
}
__device__ __forceinline__ bool mbar_try(uint32_t a, uint32_t parity) {
    uint32_t ok;
    asm volatile("{\n.reg .pred p;\nmbarrier.try_wait.parity.shared::cta.b64 p, [%1], %2;\nselp.u32 %0, 1, 0, p;\n}"
                 : "=r"(ok) : "r"(a), "r"(parity) : "memory");
    return ok != 0;
}
__device__ __forceinline__ bool mbar_try_ns(uint32_t a, uint32_t parity, uint32_t ns) {
    uint32_t ok;
    asm volatile("{\n.reg .pred p;\nmbarrier.try_wait.parity.shared::cta.b64 p, [%1], %2, %3;\nselp.u32 %0, 1, 0, p;\n}"
                 : "=r"(ok) : "r"(a), "r"(parity), "r"(ns) : "memory");
    return ok != 0;
}
__device__ __forceinline__ void mbar_wait(uint32_t a, uint32_t parity) {
    unsigned n = 0;
    while (!mbar_try(a, parity)) {
        if (++n > SPIN_LIMIT) __trap();
    }
}
__device__ __forceinline__ void tma2d_plain(uint32_t dst, const CUtensorMap* tm, int c0, int c1, uint32_t bar) {
    asm volatile("cp.async.bulk.tensor.2d.shared::cluster.global.mbarrier::complete_tx::bytes [%0], [%1, {%3, %4}], [%2];"
                 ::"r"(dst), "l"(tm), "r"(bar), "r"(c0), "r"(c1) : "memory");
}
__device__ __forceinline__ void tma3d(uint32_t dst, const CUtensorMap* tm, int c0, int c1, int c2, uint32_t bar, uint64_t pol) {
    asm volatile("cp.async.bulk.tensor.3d.shared::cluster.global.mbarrier::complete_tx::bytes.L2::cache_hint [%0], [%1, {%3, %4, %5}], [%2], %6;"
                 ::"r"(dst), "l"(tm), "r"(bar), "r"(c0), "r"(c1), "r"(c2), "l"(pol) : "memory");
}
__device__ __forceinline__ void prefetch_tmap(const CUtensorMap* tm) {
    asm volatile("prefetch.tensormap [%0];" ::"l"(tm) : "memory");
}
__device__ __forceinline__ void cons_sync() { asm volatile("bar.sync 1, 256;" ::: "memory"); }

__device__ __forceinline__ uint4 lds128(uint32_t a) {
    uint4 v;
    asm volatile("ld.shared.v4.u32 {%0, %1, %2, %3}, [%4];" : "=r"(v.x), "=r"(v.y), "=r"(v.z), "=r"(v.w) : "r"(a) : "memory");
    return v;
}
__device__ __forceinline__ void ldsm4(uint32_t a, uint32_t& r0, uint32_t& r1, uint32_t& r2, uint32_t& r3) {
    asm volatile("ldmatrix.sync.aligned.m8n8.x4.shared.b16 {%0, %1, %2, %3}, [%4];"
                 : "=r"(r0), "=r"(r1), "=r"(r2), "=r"(r3) : "r"(a));
}
__device__ __forceinline__ void ldsm4t(uint32_t a, uint32_t& r0, uint32_t& r1, uint32_t& r2, uint32_t& r3) {
    asm volatile("ldmatrix.sync.aligned.m8n8.x4.trans.shared.b16 {%0, %1, %2, %3}, [%4];"
                 : "=r"(r0), "=r"(r1), "=r"(r2), "=r"(r3) : "r"(a));
}
__device__ __forceinline__ void mma16816(float (&c)[4], uint32_t a0, uint32_t a1, uint32_t a2, uint32_t a3,
                                         uint32_t b0, uint32_t b1) {
    asm volatile("mma.sync.aligned.m16n8k16.row.col.f32.bf16.bf16.f32 {%0, %1, %2, %3}, {%4, %5, %6, %7}, {%8, %9}, {%0, %1, %2, %3};"
                 : "+f"(c[0]), "+f"(c[1]), "+f"(c[2]), "+f"(c[3])
                 : "r"(a0), "r"(a1), "r"(a2), "r"(a3), "r"(b0), "r"(b1));
}
__device__ __forceinline__ uint32_t movm_t(uint32_t a) {
    uint32_t d;
    asm volatile("movmatrix.sync.aligned.m8n8.trans.b16 %0, %1;" : "=r"(d) : "r"(a));
    return d;
}
__device__ __forceinline__ uint32_t pack_bf16(float lo, float hi) {
    uint32_t r;
    asm("cvt.rn.bf16x2.f32 %0, %1, %2;" : "=r"(r) : "f"(hi), "f"(lo));
    return r;
}
__device__ __forceinline__ float bf_lo(uint32_t v) { return __uint_as_float(v << 16); }
__device__ __forceinline__ float bf_hi(uint32_t v) { return __uint_as_float(v & 0xffff0000u); }
__device__ __forceinline__ float rbf(float x) { return __bfloat162float(__float2bfloat16_rn(x)); }
__device__ __forceinline__ float ex2(float x) {
    float y;
    asm("ex2.approx.ftz.f32 %0, %1;" : "=f"(y) : "f"(x));
    return y;
}
__device__ __forceinline__ void box_st1(unsigned long long* p, uint32_t payload, uint32_t epoch) {
    asm volatile("st.relaxed.gpu.global.b64 [%0], %1;" ::"l"(p), "l"(((unsigned long long)epoch << 32) | payload) : "memory");
}
__device__ __forceinline__ void box_ld2(const unsigned long long* p, unsigned long long& a, unsigned long long& b) {
    asm volatile("ld.relaxed.gpu.global.v2.b64 {%0, %1}, [%2];" : "=l"(a), "=l"(b) : "l"(p) : "memory");
}
__device__ __forceinline__ uint32_t pay(float v, uint32_t tag) { return (__float_as_uint(v) & ~TAG_MASK) | tag; }
__device__ __forceinline__ float val(uint32_t w) { return __uint_as_float(w & ~TAG_MASK); }
__device__ __forceinline__ bool tagged4(const uint4& v, uint32_t tag) {
    return (((v.x ^ tag) | (v.y ^ tag) | (v.z ^ tag) | (v.w ^ tag)) & TAG_MASK) == 0;
}
__device__ __forceinline__ void in_st1(uint32_t* p, uint32_t a) {
    asm volatile("st.relaxed.gpu.global.b32 [%0], %1;" ::"l"(p), "r"(a) : "memory");
}
__device__ __forceinline__ void in_st4(uint32_t* p, uint32_t a, uint32_t b, uint32_t c, uint32_t d) {
    asm volatile("st.relaxed.gpu.global.v4.b32 [%0], {%1, %2, %3, %4};" ::"l"(p), "r"(a), "r"(b), "r"(c), "r"(d) : "memory");
}
__device__ __forceinline__ uint4 in_ld4(const uint32_t* p) {
    uint4 v;
    asm volatile("ld.relaxed.gpu.global.v4.b32 {%0, %1, %2, %3}, [%4];" : "=r"(v.x), "=r"(v.y), "=r"(v.z), "=r"(v.w) : "l"(p) : "memory");
    return v;
}
__device__ __forceinline__ uint32_t in_ld1(const uint32_t* p) {
    uint32_t v;
    asm volatile("ld.relaxed.gpu.global.b32 %0, [%1];" : "=r"(v) : "l"(p) : "memory");
    return v;
}
__device__ __forceinline__ void fma8(float (&acc)[8], const uint4& w, float x) {
    acc[0] = fmaf(x, bf_lo(w.x), acc[0]); acc[1] = fmaf(x, bf_hi(w.x), acc[1]);
    acc[2] = fmaf(x, bf_lo(w.y), acc[2]); acc[3] = fmaf(x, bf_hi(w.y), acc[3]);
    acc[4] = fmaf(x, bf_lo(w.z), acc[4]); acc[5] = fmaf(x, bf_hi(w.z), acc[5]);
    acc[6] = fmaf(x, bf_lo(w.w), acc[6]); acc[7] = fmaf(x, bf_hi(w.w), acc[7]);
}
__device__ __forceinline__ void red_quads(float (&acc)[8]) {
#pragma unroll
    for (int i = 0; i < 8; i++) {
        acc[i] += __shfl_xor_sync(0xffffffffu, acc[i], 4);
        acc[i] += __shfl_xor_sync(0xffffffffu, acc[i], 8);
        acc[i] += __shfl_xor_sync(0xffffffffu, acc[i], 16);
    }
}
__device__ __forceinline__ float warp_sum(float v) {
#pragma unroll
    for (int o = 16; o > 0; o >>= 1) v += __shfl_xor_sync(0xffffffffu, v, o);
    return v;
}

__device__ __forceinline__ int vec_pos(int step, int e) {
    return (step * 4 + ((e >> 1) & 3)) * 32 + (e >> 4) * 4 + ((e >> 3) & 1) * 2 + (e & 1);
}
template <int W>
__device__ __forceinline__ void fold(float (&v)[32], int lane) {
    const bool up = lane & W;
#pragma unroll
    for (int i = 0; i < W; i++) {
        const float keep = up ? v[W + i] : v[i], send = up ? v[i] : v[W + i];
        v[i] = keep + __shfl_xor_sync(0xffffffffu, send, W);
    }
}

struct Maps { CUtensorMap k, v, q, g, u, d, o; };

__global__ void __launch_bounds__(NTHREADS, 1)
fused_decode_kernel(const __grid_constant__ Maps tm, const __nv_bfloat16* __restrict__ x,
                    const __nv_bfloat16* __restrict__ wq,
                    __nv_bfloat16* __restrict__ out) {
    extern __shared__ unsigned char smem_raw[];
    unsigned char* smem = smem_raw + ((1024u - (smem_u32(smem_raw) & 1023u)) & 1023u);
    const uint32_t sbase = smem_u32(smem);
    const uint32_t bar_fullA = sbase + OFF_BAR;
    const uint32_t bar_fullB = bar_fullA + 8 * STAGES;
    const uint32_t bar_empty = bar_fullB + 8 * STAGES;
    const uint32_t bar_kv = bar_empty + 8 * STAGES;
    const uint32_t bar_pub = bar_kv + 8;

    const int tid = threadIdx.x, warp = tid >> 5, lane = tid & 31;
    const int cta = blockIdx.x, grp = cta / CPG, gj = cta % CPG;
    const int rho = cta / RG, kap = cta % RG;
#define START_COND (tid == 256)
    if (START_COND) {
#pragma unroll
        for (int v = 0; v < 4; v++) {
            const uint32_t bar = ((v & 1) ? bar_fullB : bar_fullA) + 8 * (v >> 1);
            mbar_init(bar, 1);
            mbar_expect_tx(bar, HALF_BYTES);
            tma2d_plain(sbase + v * HALF_BYTES, &tm.q, cta * 32, v * 256, bar);
        }
        PROF(14);
    }
    uint32_t epoch_raw;
    asm volatile("ld.relaxed.gpu.global.u32 %0, [%1];" : "=r"(epoch_raw) : "l"(&g_epoch) : "memory");
    uint32_t* const inbox = &g_inbox[cta * BOX_WORDS];

    if (warp == 8) {
        const int key0 = grp * S_K + gj * TILE_KEYS;
        uint64_t pol;
        asm volatile("createpolicy.fractional.L2::evict_first.b64 %0, 1.0;" : "=l"(pol));
        int4* tab = reinterpret_cast<int4*>(smem + OFF_TAB);
        for (int v = 4 + lane; v < 2 * N_STEPS; v += 32) {
            const int n = v >> 1, hb = v & 1;
            int4 e;
            if (n < GU0) e = make_int4(hb | (HALF_BYTES << 8), 0, key0 + (n - KV0) * (CPG * TILE_KEYS), 0);
            else if (n < WO0) e = make_int4((3 + hb) | (SMALL_BYTES << 8), rho * FF_G, GU_ROW(kap, n - GU0), 0);
            else if (n < DN0) e = make_int4(6 | (HALF_BYTES << 8), 0, rho * 256 + (v - 2 * WO0) * 64, 2 * kap);
            else e = make_int4(5 | (SMALL_BYTES << 8), 0, rho * FF_G + (v - 2 * DN0) * 56, 2 * kap);
            tab[v] = e;
        }
        auto issue = [&](int v) {
            const int s = (v >> 1) % STAGES, hb = v & 1;
            const int4 e = tab[v];
            const uint32_t bar = (hb ? bar_fullB : bar_fullA) + 8 * s;
            mbar_expect_tx(bar, e.x >> 8);
            tma3d(sbase + s * STAGE_BYTES + hb * HALF_BYTES, &tm.k + (e.x & 7), e.y, e.z, e.w, bar, pol);
        };
        if (lane == 0) {
            PROF(0);
            GT(0);
#pragma unroll
            for (int s = 0; s < STAGES; s++) {
                if (s >= 2) {
                    mbar_init(bar_fullA + 8 * s, 1);
                    mbar_init(bar_fullB + 8 * s, 1);
                }
                mbar_init(bar_empty + 8 * s, 4);
            }
            mbar_init(bar_kv, V_PROBE >= 0 ? 9 : 8);
            mbar_init(bar_pub, 8);
            asm volatile("fence.mbarrier_init.release.cluster;" ::: "memory");
        } else if (lane < 7) {
            prefetch_tmap(&tm.k + (lane == 1 ? 0 : lane == 2 ? 1 : lane));
        }
        __syncwarp();
        asm volatile("bar.arrive 2, 320;" ::: "memory");
        if (lane == 0) {
            constexpr int N_COUNTS = (SPARSE0 - CNT0) / 2 + (CNT1 - SPARSE0) / SPARSE_STEP;
            int landed = 0, next = CNT0, mine = NCTA / 2, win = WIN;
            for (int v = 4; v < 2 * N_STEPS || next < CNT1; v++) {
                while (landed <= v - win) {
                    const int wn = landed >> 1;
                    mbar_wait(((landed & 1) ? bar_fullB : bar_fullA) + 8 * (wn % STAGES), (wn / STAGES) & 1);
                    LAND(landed);
                    landed++;
                }
                if (v < 2 * N_STEPS) {
                    const int n = v >> 1;
                    if (!(v & 1) && n >= STAGES) mbar_wait(bar_empty + 8 * (n % STAGES), ((n / STAGES) & 1) ^ 1);
                    issue(v);
                    if (v == 2 * GU0 - 1) PROF(1);
                    if (V_PROBE >= 0 && v == 2 * GU0 + V_PROBE) mbar_arrive(bar_kv);
                }
                if (landed > next && next < CNT1) {
                    const uint32_t seen = atomicAdd(&g_count, 1u) - epoch_raw * (uint32_t)(NCTA * N_COUNTS);
                    const int lead = (mine - (int)seen) * (next > SPARSE0 ? SPARSE_STEP / 2 : 1);
                    win = lead > BAL_T ? WIN - 1 : (lead < -BAL_TL ? WIN + BAL_UP : WIN);
                    if (landed >= TAILU && win < WIN_TAIL) win = WIN_TAIL;
                    if (landed >= GU_BUMP0 && landed < GU_BUMP1) win++;
                    mine += NCTA;
                    next += next >= SPARSE0 ? SPARSE_STEP : 2;
                }
            }
            PROF(12);
        }
        return;
    }

    if (warp == 9) {
        const uint32_t epoch = epoch_raw + 1, tag = epoch & TAG_MASK;
        const int ocol = kap * 128 + rho * 8 + (lane & 1) * 4 + (lane >> 4) * 2 + ((lane >> 3) & 1);
        const float xres = __bfloat162float(x[ocol]);
        {
            const uint32_t e = tag ^ 8u;
#pragma unroll
            for (int i = 0; i < 4; i++)
                if (i * 128 + lane * 4 < OUT_WORDS) in_st4(&g_outbox[cta * OUT_WORDS + i * 128 + lane * 4], e, e, e, e);
            if (lane < 16) box_st1(&g_qbox[cta * 16 + lane], 0, epoch_raw);
        }
        asm volatile("bar.sync 2, 320;" ::: "memory");
        unsigned n = 0;
        mbar_wait(bar_kv, 0);
        {
            const uint32_t* src = inbox + lane * P_REC;
            uint4 a[8], ml;
            while (true) {
                ml = in_ld4(src + 32);
                if (tagged4(ml, tag)) break;
                if (++n > SPIN_LIMIT) __trap();
                __nanosleep(PROBE_NS);
            }
            while (true) {
#pragma unroll
                for (int i = 0; i < 8; i++) a[i] = in_ld4(src + 4 * i);
                bool ok = true;
#pragma unroll
                for (int i = 0; i < 8; i++) ok = ok && tagged4(a[i], tag);
                if (ok) break;
                if (++n > SPIN_LIMIT) __trap();
                __nanosleep(300);
            }
            __syncwarp();
            const float m = val(ml.x);
            int key = __float_as_int(m);
            key = key >= 0 ? key : key ^ 0x7fffffff;
            key = __reduce_max_sync(0xffffffffu, key);
            key = key >= 0 ? key : key ^ 0x7fffffff;
            const float wgt = ex2((m - __int_as_float(key)) * LOG2E);
            const float L = warp_sum(val(ml.y) * wgt);
            float v[32];
#pragma unroll
            for (int i = 0; i < 8; i++) {
                v[4 * i] = val(a[i].x) * wgt; v[4 * i + 1] = val(a[i].y) * wgt;
                v[4 * i + 2] = val(a[i].z) * wgt; v[4 * i + 3] = val(a[i].w) * wgt;
            }
            fold<16>(v, lane); fold<8>(v, lane); fold<4>(v, lane); fold<2>(v, lane); fold<1>(v, lane);
            const uint32_t ob = pack_bf16(0.f, __fdiv_rn(v[0], L));
            in_st1(&g_outbox[cta * OUT_WORDS + OUT_O + lane], ob | tag);
            if (lane == 0) PROF(8);
        }
        const uint32_t* src = inbox + BOX_O + lane * 4;
#pragma unroll 1
        for (int pass = DRY0; pass < 2; pass++) {
            uint4 a = in_ld4(src);
            if (pass) {
                while (!tagged4(a, tag) && !mbar_try_ns(bar_pub, 0, POLL_NS)) {
                    a = in_ld4(src);
                    if (++n > SPIN_LIMIT) __trap();
                }
                while (!tagged4(a, tag)) {
                    a = in_ld4(src);
                    if (++n > SPIN_LIMIT) __trap();
                }
            }
            __syncwarp();
            const bool b4 = lane & 16, b3 = lane & 8;
            float v0 = (b4 ? val(a.z) : val(a.x)) + __shfl_xor_sync(0xffffffffu, b4 ? val(a.x) : val(a.z), 16);
            float v1 = (b4 ? val(a.w) : val(a.y)) + __shfl_xor_sync(0xffffffffu, b4 ? val(a.y) : val(a.w), 16);
            float r = (b3 ? v1 : v0) + __shfl_xor_sync(0xffffffffu, b3 ? v0 : v1, 8);
            r += __shfl_xor_sync(0xffffffffu, r, 4);
            r += __shfl_xor_sync(0xffffffffu, r, 2);
            if (pass && (lane & 6) == 0) out[ocol] = __float2bfloat16_rn(xres + r);
        }
        if (cta == 0 && lane == 0) g_epoch = epoch;
        if (lane == 0) { PROF(11); GT(1); }
        return;
    }

    float* xn = reinterpret_cast<float*>(smem + OFF_XN);
    const int g = lane >> 2, t = lane & 3;
    uint2 xraw;
    asm volatile("ld.global.nc.v2.u32 {%0, %1}, [%2];" : "=r"(xraw.x), "=r"(xraw.y) : "l"(x + tid * 4));
    const uint32_t epoch = epoch_raw + 1, tag = epoch & TAG_MASK;
    {
        float* ln = reinterpret_cast<float*>(smem + OFF_LN);
        const float x0 = bf_lo(xraw.x), x1 = bf_hi(xraw.x), x2 = bf_lo(xraw.y), x3 = bf_hi(xraw.y);
        float s = warp_sum((x0 + x1) + (x2 + x3));
        if (lane == 0) ln[warp] = s;
        asm volatile("bar.sync 2, 320;" ::: "memory");
        float tot = 0.f;
#pragma unroll
        for (int i = 0; i < 8; i++) tot += ln[i];
        const float mean = tot * (1.0f / D_MODEL);
        const float d0 = x0 - mean, d1 = x1 - mean, d2 = x2 - mean, d3 = x3 - mean;
        float v = warp_sum((d0 * d0 + d1 * d1) + (d2 * d2 + d3 * d3));
        if (lane == 0) ln[8 + warp] = v;
        cons_sync();
        float vt = 0.f;
#pragma unroll
        for (int i = 0; i < 8; i++) vt += ln[8 + i];
        const float mb = rbf(mean);
        const float sd = rbf(__fsqrt_rn(rbf(rbf(vt * (1.0f / D_MODEL)) + 1e-5f)));
        float4 o;
        o.x = rbf(__fdiv_rn(rbf(x0 - mb), sd));
        o.y = rbf(__fdiv_rn(rbf(x1 - mb), sd));
        o.z = rbf(__fdiv_rn(rbf(x2 - mb), sd));
        o.w = rbf(__fdiv_rn(rbf(x3 - mb), sd));
        reinterpret_cast<float4*>(xn)[tid] = o;
        reinterpret_cast<uint2*>(smem + OFF_XB)[tid] = make_uint2(pack_bf16(o.x, o.y), pack_bf16(o.z, o.w));
        cons_sync();
    }
    const int half = warp >> 2;
    const int gt = tid & 127;
    uint32_t qf[8][2];
    {
        float acc[8] = {0.f, 0.f, 0.f, 0.f, 0.f, 0.f, 0.f, 0.f};
        const uint32_t a = sbase + half * STAGE_BYTES + gt * 16;
        const float* xr = xn + half * 512 + (gt >> 2);
        mbar_wait(bar_fullA + 8 * half, 0);
#pragma unroll
        for (int i = 0; i < 8; i++) fma8(acc, lds128(a + i * 2048), xr[32 * i]);
        mbar_wait(bar_fullB + 8 * half, 0);
#pragma unroll
        for (int i = 0; i < 8; i++) fma8(acc, lds128(a + HALF_BYTES + i * 2048), xr[256 + 32 * i]);
        __syncwarp();
        if (lane == 0) mbar_arrive(bar_empty + 8 * half);
        red_quads(acc);
        float* rq = reinterpret_cast<float*>(smem + OFF_REDQ);
        if (lane < 4) {
            reinterpret_cast<float4*>(rq + warp * 32 + lane * 8)[0] = make_float4(acc[0], acc[1], acc[2], acc[3]);
            reinterpret_cast<float4*>(rq + warp * 32 + lane * 8)[1] = make_float4(acc[4], acc[5], acc[6], acc[7]);
        }
        cons_sync();
        if (tid < 16) {
            float qa = 0.f, qb = 0.f;
#pragma unroll
            for (int w = 0; w < 8; w++) { qa += rq[w * 32 + 2 * tid]; qb += rq[w * 32 + 2 * tid + 1]; }
            box_st1(&g_qbox[cta * 16 + tid], pack_bf16(qa, qb), epoch);
        }
        const unsigned long long* src = &g_qbox[grp * 512 + 2 * tid];
        unsigned long long qa, qb;
        unsigned n = 0;
        while (true) {
            box_ld2(src, qa, qb);
            if ((uint32_t)(qa >> 32) == epoch && (uint32_t)(qb >> 32) == epoch) break;
            if (++n > SPIN_LIMIT) __trap();
            __nanosleep(100);
        }
        uint32_t* qs = reinterpret_cast<uint32_t*>(smem + OFF_Q);
        reinterpret_cast<uint2*>(qs)[tid] = make_uint2((uint32_t)qa, (uint32_t)qb);
        cons_sync();
#pragma unroll
        for (int ks = 0; ks < 8; ks++) {
            qf[ks][0] = qs[g * 64 + ks * 8 + t];
            qf[ks][1] = qs[g * 64 + ks * 8 + 4 + t];
        }
    }
    if (tid == 0) PROF(5);

    {
        float o[8][4];
#pragma unroll
        for (int i = 0; i < 8; i++) o[i][0] = o[i][1] = o[i][2] = o[i][3] = 0.f;
        float m0 = -INFINITY, m1 = -INFINITY, l0 = 0.f, l1 = 0.f;
        const int kw = (warp & 3) * 16, r7 = lane & 7, mi = lane >> 3;
        const uint32_t k_row = (kw + r7 + 8 * (mi & 1)) * 128;
        const uint32_t v_row = HALF_BYTES + (kw + r7 + 8 * (mi >> 1)) * 128;
        uint32_t k_off[4], v_off[4];
#pragma unroll
        for (int j = 0; j < 4; j++) {
            k_off[j] = k_row + (((2 * j + (mi >> 1)) ^ r7) << 4);
            v_off[j] = v_row + (((2 * j + (mi & 1)) ^ r7) << 4);
        }
        for (int n = KV0 + half; n < GU0; n += 2) {
            const int s = n % STAGES;
            const uint32_t ph = (n / STAGES) & 1;
            const uint32_t base = sbase + s * STAGE_BYTES;
            float sa[4] = {0.f, 0.f, 0.f, 0.f}, sb[4] = {0.f, 0.f, 0.f, 0.f};
            mbar_wait(bar_fullA + 8 * s, ph);
#pragma unroll
            for (int j = 0; j < 4; j++) {
                uint32_t a0, a1, a2, a3, c0, c1, c2, c3;
                ldsm4(base + k_off[j], a0, a1, a2, a3);
                ldsm4(base + k_off[j] + 8192, c0, c1, c2, c3);
                mma16816(sa, a0, a1, a2, a3, qf[j][0], qf[j][1]);
                mma16816(sb, c0, c1, c2, c3, qf[4 + j][0], qf[4 + j][1]);
            }
            const uint32_t r01 = pack_bf16(sa[0] + sb[0], sa[1] + sb[1]);
            const uint32_t r23 = pack_bf16(sa[2] + sb[2], sa[3] + sb[3]);
            const uint32_t u01 = pack_bf16(bf_lo(r01) * SM_SCALE, bf_hi(r01) * SM_SCALE);
            const uint32_t u23 = pack_bf16(bf_lo(r23) * SM_SCALE, bf_hi(r23) * SM_SCALE);
            const float s0 = bf_lo(u01), s1 = bf_hi(u01), s2 = bf_lo(u23), s3 = bf_hi(u23);
            float t0 = fmaxf(s0, s2), t1 = fmaxf(s1, s3);
#pragma unroll
            for (int sh = 4; sh <= 16; sh <<= 1) {
                t0 = fmaxf(t0, __shfl_xor_sync(0xffffffffu, t0, sh));
                t1 = fmaxf(t1, __shfl_xor_sync(0xffffffffu, t1, sh));
            }
            if (__any_sync(0xffffffffu, t0 > m0 || t1 > m1)) {
                const float n0 = fmaxf(m0, t0), n1 = fmaxf(m1, t1);
                const float f0 = ex2((m0 - n0) * LOG2E), f1 = ex2((m1 - n1) * LOG2E);
                m0 = n0; m1 = n1;
                l0 *= f0; l1 *= f1;
#pragma unroll
                for (int i = 0; i < 8; i++) { o[i][0] *= f0; o[i][1] *= f1; o[i][2] *= f0; o[i][3] *= f1; }
            }
            const float p0 = ex2((s0 - m0) * LOG2E), p1 = ex2((s1 - m1) * LOG2E);
            const float p2 = ex2((s2 - m0) * LOG2E), p3 = ex2((s3 - m1) * LOG2E);
            l0 += p0 + p2;
            l1 += p1 + p3;
            const uint32_t b0 = movm_t(pack_bf16(p0, p1));
            const uint32_t b1 = movm_t(pack_bf16(p2, p3));
            mbar_wait(bar_fullB + 8 * s, ph);
#pragma unroll
            for (int j = 0; j < 4; j++) {
                uint32_t a0, a1, a2, a3, c0, c1, c2, c3;
                ldsm4t(base + v_off[j], a0, a1, a2, a3);
                ldsm4t(base + v_off[j] + 8192, c0, c1, c2, c3);
                mma16816(o[j], a0, a1, a2, a3, b0, b1);
                mma16816(o[4 + j], c0, c1, c2, c3, b0, b1);
            }
            __syncwarp();
            if (lane == 0) mbar_arrive(bar_empty + 8 * s);
        }
        if (tid == 0) PROF(6);

        float* ms = reinterpret_cast<float*>(smem + OFF_MS);
        float* ls = reinterpret_cast<float*>(smem + OFF_LS);
        float* mrg = reinterpret_cast<float*>(smem + OFF_MRG);
        if (g == 0) reinterpret_cast<float2*>(ms + warp * 8)[t] = make_float2(m0, m1);
#pragma unroll
        for (int sh = 4; sh <= 16; sh <<= 1) {
            l0 += __shfl_xor_sync(0xffffffffu, l0, sh);
            l1 += __shfl_xor_sync(0xffffffffu, l1, sh);
        }
        cons_sync();
        float M0 = -INFINITY, M1 = -INFINITY;
#pragma unroll
        for (int w = 0; w < 8; w++) {
            const float2 v = reinterpret_cast<const float2*>(ms + w * 8)[t];
            M0 = fmaxf(M0, v.x); M1 = fmaxf(M1, v.y);
        }
        const float f0 = ex2((m0 - M0) * LOG2E), f1 = ex2((m1 - M1) * LOG2E);
        if (g == 0) reinterpret_cast<float2*>(ls + warp * 8)[t] = make_float2(l0 * f0, l1 * f1);
        float* dst = mrg + warp * MRG_WS + 2 * t * MRG_HS + g;
#pragma unroll
        for (int i = 0; i < 8; i++) {
            dst[16 * i] = o[i][0] * f0;
            dst[16 * i + MRG_HS] = o[i][1] * f1;
            dst[16 * i + 8] = o[i][2] * f0;
            dst[16 * i + 8 + MRG_HS] = o[i][3] * f1;
        }
        cons_sync();
        float a0 = 0.f, a1 = 0.f, a2 = 0.f, a3 = 0.f, L = 0.f, M = -INFINITY;
#pragma unroll
        for (int w = 0; w < 8; w++) {
            const float4 u = *reinterpret_cast<const float4*>(mrg + w * MRG_WS + warp * MRG_HS + 4 * lane);
            a0 += u.x; a1 += u.y; a2 += u.z; a3 += u.w;
            L += ls[w * 8 + warp];
            M = fmaxf(M, ms[w * 8 + warp]);
        }
        uint32_t* pb = &g_inbox[(grp * CPG + warp * 4) * BOX_WORDS + gj * P_REC];
        in_st4(pb + (lane >> 3) * BOX_WORDS + (lane & 7) * 4, pay(a0, tag), pay(a1, tag), pay(a2, tag), pay(a3, tag));
        if (lane < 8)
            in_st4(pb + (lane >> 1) * BOX_WORDS + 32 + (lane & 1) * 4, pay(M, tag), pay(L, tag), pay(M, tag), pay(L, tag));
        __syncwarp();
        if (lane == 0) mbar_arrive(bar_kv);
    }
    if (tid == 0) PROF(7);

    {
        float cg[7][4], cu[7][4];
#pragma unroll
        for (int i = 0; i < 7; i++) {
            cg[i][0] = cg[i][1] = cg[i][2] = cg[i][3] = 0.f;
            cu[i][0] = cu[i][1] = cu[i][2] = cu[i][3] = 0.f;
        }
        const int ks = warp & 1, mg = (warp >> 1) & 1, mi = lane >> 3;
        const uint32_t a_off = (ks * 16 + (lane & 7) + 8 * (mi >> 1)) * (FF_G * 2) + (mg * 14 + (mi & 1)) * 16;
        const uint32_t* xb = reinterpret_cast<const uint32_t*>(smem + OFF_XB) + ks * 8 + t;
#pragma unroll
        for (int k = 0; k < 2; k++) {
            const int n = GU0 + 2 * k + half;
            const int s = n % STAGES;
            const uint32_t ph = (n / STAGES) & 1;
            const uint32_t a = sbase + s * STAGE_BYTES + a_off;
            const uint32_t b0 = xb[GU_ROW(kap, n - GU0) / 2], b1 = xb[GU_ROW(kap, n - GU0) / 2 + 4];
            mbar_wait(bar_fullA + 8 * s, ph);
#pragma unroll
            for (int i = 0; i < 7; i++) {
                uint32_t a0, a1, a2, a3;
                ldsm4t(a + i * 32, a0, a1, a2, a3);
                mma16816(cg[i], a0, a1, a2, a3, b0, b1);
            }
            mbar_wait(bar_fullB + 8 * s, ph);
#pragma unroll
            for (int i = 0; i < 7; i++) {
                uint32_t a0, a1, a2, a3;
                ldsm4t(a + HALF_BYTES + i * 32, a0, a1, a2, a3);
                mma16816(cu[i], a0, a1, a2, a3, b0, b1);
            }
            __syncwarp();
            if (lane == 0) mbar_arrive(bar_empty + 8 * s);
        }
        float* rg = reinterpret_cast<float*>(smem + OFF_REDG);
        if (t < 2) {
            float* dst = rg + (half * 2 + ks) * (2 * FF_G) + t * FF_G + mg * 112 + g;
#pragma unroll
            for (int i = 0; i < 7; i++) {
                dst[16 * i] = t ? cu[i][0] : cg[i][0];
                dst[16 * i + 8] = t ? cu[i][2] : cg[i][2];
            }
        }
        cons_sync();
        if (tid < 2 * FF_G / 4) {
            const float4* p = reinterpret_cast<const float4*>(rg) + tid;
            const float4 u0 = p[0], u1 = p[112], u2 = p[224], u3 = p[336];
            in_st4(&g_outbox[cta * OUT_WORDS + 4 * tid], pay((u0.x + u1.x) + (u2.x + u3.x), tag),
                   pay((u0.y + u1.y) + (u2.y + u3.y), tag), pay((u0.z + u1.z) + (u2.z + u3.z), tag),
                   pay((u0.w + u1.w) + (u2.w + u3.w), tag));
        }
    }
    if (tid == 0) PROF(4);

    {
        float c0[4] = {0.f, 0.f, 0.f, 0.f}, c1[4] = {0.f, 0.f, 0.f, 0.f};
        uint32_t* const dst = &g_inbox[((2 * warp + (t & 1)) * RG + kap) * BOX_WORDS + BOX_O + rho * 8 + g];
        const int mi = lane >> 3, r7 = lane & 7;
        const uint32_t l_off = r7 * 128 + (((2 * (warp & 3) + (mi & 1)) ^ r7) << 4) + (mi >> 1) * 1024;
        {
            const uint32_t* hb = &g_outbox[rho * RG * OUT_WORDS + min(tid, FF_G - 1)];
            const uint32_t* src = &g_outbox[(rho * RG + warp) * OUT_WORDS + OUT_O + lane];
            uint32_t gw[RG], uw[RG], w = tag ^ 1;
#pragma unroll
            for (int j = 0; j < RG; j++) gw[j] = uw[j] = w;
            unsigned n = 0;
            while (true) {
                uint32_t bad = 0;
                if ((w ^ tag) & TAG_MASK) { bad = 1; w = in_ld1(src); }
#pragma unroll
                for (int j = 0; j < RG; j++) {
                    if (((gw[j] ^ tag) | (uw[j] ^ tag)) & TAG_MASK) {
                        bad = 1;
                        gw[j] = in_ld1(hb + j * OUT_WORDS);
                        uw[j] = in_ld1(hb + j * OUT_WORDS + FF_G);
                    }
                }
                if (!bad) break;
                if (++n > SPIN_LIMIT) __trap();
            }
            if (tid == 0) PROF(2);
            reinterpret_cast<uint16_t*>(smem + OFF_VEC)[vec_pos(tid >> 7, tid & 127)] = (uint16_t)(w >> 16);
            float gsum = 0.f, usum = 0.f;
#pragma unroll
            for (int j = 0; j < RG; j++) { gsum += val(gw[j]); usum += val(uw[j]); }
            const float gb = rbf(gsum), ub = rbf(usum);
            const float inner = 0.7978845608028654f * (gb + 0.044715f * gb * gb * gb);
            const float ge = rbf(0.5f * gb * (1.0f + tanhf(inner)));
            const int hi = tid >= 112;
            if (tid < FF_G)
                reinterpret_cast<__nv_bfloat16*>(smem + OFF_VEC)[vec_pos(2 + hi, tid - hi * 112)] = __float2bfloat16_rn(ge * ub);
            cons_sync();
            if (tid == 0) PROF(13);
        }
#pragma unroll 1
        for (int k = 0; k < 4; k++) {
            const int st = WO0 + k, s = st % STAGES, G = k < 2 ? 8 : 7;
            const uint32_t ph = (st / STAGES) & 1;
            const uint32_t vk = sbase + OFF_VEC + (k * 4 + t) * 64;
            const uint4 b0 = lds128(vk), b1 = lds128(vk + 16), b2 = lds128(vk + 32), b3 = lds128(vk + 48);
            const uint32_t ua = sbase + s * STAGE_BYTES + (warp >> 2) * (G * 1024) + l_off;
            const uint32_t ub = ua + HALF_BYTES - G * 1024;
            uint32_t a0, a1, a2, a3;
            mbar_wait(bar_fullA + 8 * s, ph);
            ldsm4t(ua, a0, a1, a2, a3);        mma16816(c0, a0, a1, a2, a3, b0.x, b0.y);
            ldsm4t(ua + 2048, a0, a1, a2, a3); mma16816(c1, a0, a1, a2, a3, b0.z, b0.w);
            ldsm4t(ua + 4096, a0, a1, a2, a3); mma16816(c0, a0, a1, a2, a3, b1.x, b1.y);
            mbar_wait(bar_fullB + 8 * s, ph);
            if (k == 3 && tid == 0) PROF(9);
            if (k == 0 && tid == 0) PROF(3);
            ldsm4t((6 + (mi >> 1) >= G ? ub : ua) + 6144, a0, a1, a2, a3); mma16816(c1, a0, a1, a2, a3, b1.z, b1.w);
            ldsm4t(ub + 8192, a0, a1, a2, a3);  mma16816(c0, a0, a1, a2, a3, b2.x, b2.y);
            ldsm4t(ub + 10240, a0, a1, a2, a3); mma16816(c1, a0, a1, a2, a3, b2.z, b2.w);
            ldsm4t(ub + 12288, a0, a1, a2, a3); mma16816(c0, a0, a1, a2, a3, b3.x, b3.y);
            if (k < 2) { ldsm4t(ub + 14336, a0, a1, a2, a3); mma16816(c1, a0, a1, a2, a3, b3.z, b3.w); }
            if (k == 3 && t < 2) in_st1(dst, pay(t ? c0[2] + c1[2] : c0[0] + c1[0], tag));
        }
        if (tid == 0) PROF(10);
        __syncwarp();
        if (lane == 0) mbar_arrive(bar_pub);
    }
}

typedef CUresult (*EncodeFn)(CUtensorMap*, CUtensorMapDataType, cuuint32_t, void*, const cuuint64_t*, const cuuint64_t*,
                             const cuuint32_t*, const cuuint32_t*, CUtensorMapInterleave, CUtensorMapSwizzle,
                             CUtensorMapL2promotion, CUtensorMapFloatOOBfill);

void map_blocks(EncodeFn enc, CUtensorMap* m, void* p, uint64_t rows, uint32_t row_elems, uint32_t box_rows) {
    const cuuint64_t gd[3] = {64, rows, row_elems / 64};
    const cuuint64_t gs[2] = {(cuuint64_t)row_elems * 2, 128};
    const cuuint32_t bd[3] = {64, box_rows, 2};
    const cuuint32_t es[3] = {1, 1, 1};
    enc(m, CU_TENSOR_MAP_DATA_TYPE_BFLOAT16, 3, p, gd, gs, bd, es, CU_TENSOR_MAP_INTERLEAVE_NONE,
        CU_TENSOR_MAP_SWIZZLE_128B, KV_PROMO, CU_TENSOR_MAP_FLOAT_OOB_FILL_NONE);
}
void map_cols(EncodeFn enc, CUtensorMap* m, void* p, int rank, uint64_t cols, uint32_t box_cols, uint32_t box_rows,
              CUtensorMapL2promotion promo) {
    const cuuint64_t gd[3] = {cols, D_MODEL, 1};
    const cuuint64_t gs[2] = {cols * 2, cols * 2 * D_MODEL};
    const cuuint32_t bd[3] = {box_cols, box_rows, 1};
    const cuuint32_t es[3] = {1, 1, 1};
    enc(m, CU_TENSOR_MAP_DATA_TYPE_BFLOAT16, rank, p, gd, gs, bd, es, CU_TENSOR_MAP_INTERLEAVE_NONE,
        CU_TENSOR_MAP_SWIZZLE_NONE, promo, CU_TENSOR_MAP_FLOAT_OOB_FILL_NONE);
}

}

extern "C" void kernel_launch(void* const* d_in, const int* in_sizes, int n_in, void* d_out, int out_size) {
    (void)in_sizes; (void)n_in; (void)out_size;
    static EncodeFn encode = nullptr;
    if (!encode) {
        void* fn = nullptr;
        cudaDriverEntryPointQueryResult qr;
        cudaGetDriverEntryPoint("cuTensorMapEncodeTiled", &fn, cudaEnableDefault, &qr);
        encode = (EncodeFn)fn;
        cudaFuncSetAttribute(fused_decode_kernel, cudaFuncAttributeMaxDynamicSharedMemorySize, SMEM_BYTES);
    }
    Maps tm;
    map_blocks(encode, &tm.k, d_in[1], (uint64_t)N_HKV * S_K, 128, TILE_KEYS);
    map_blocks(encode, &tm.v, d_in[2], (uint64_t)N_HKV * S_K, 128, TILE_KEYS);
    map_cols(encode, &tm.q, d_in[3], 2, QCOLS, 32, 256, CU_TENSOR_MAP_L2_PROMOTION_L2_128B);
    map_cols(encode, &tm.g, d_in[6], 3, D_FF, FF_G, 32, GU_PROMO);
    map_cols(encode, &tm.u, d_in[7], 3, D_FF, FF_G, 32, GU_PROMO);
    map_blocks(encode, &tm.d, d_in[8], D_FF, D_MODEL, 56);
    map_blocks(encode, &tm.o, d_in[4], QCOLS, D_MODEL, 64);
    fused_decode_kernel<<<NCTA, NTHREADS, SMEM_BYTES, cudaStreamPerThread>>>(
        tm, (const __nv_bfloat16*)d_in[0], (const __nv_bfloat16*)d_in[3],
        (__nv_bfloat16*)d_out);
}
```

```cpp
#include <cuda_runtime.h>
#include <cuda_bf16.h>
#include <cuda.h>
#include <stdint.h>

namespace {

constexpr int D_MODEL = 1024;
constexpr int N_HKV = 4;
constexpr int S_K = 65536;
constexpr int D_FF = 3584;
constexpr int QCOLS = 4096;

constexpr int NCTA = 128;
constexpr int CPG = 32;
constexpr int TILE_KEYS = 64;
constexpr int KV_TILES = S_K / CPG / TILE_KEYS;
constexpr int KV0 = 2;
constexpr int GU0 = KV0 + KV_TILES;
constexpr int WO0 = GU0 + 4;
constexpr int DN0 = WO0 + 2;
constexpr int N_STEPS = DN0 + 2;
constexpr int STAGES = 4;
#define WIN 3
#define WIN_TAIL WIN
#define TAIL0 WO0
#define KV_PROMO CU_TENSOR_MAP_L2_PROMOTION_L2_256B
#define DELAY_O 0
#define PROBE_NS 300
#define V_PROBE 6
#define DRY0 0
#define BAL_T 96
#define BAL_TL 32
#define TAILU 1000
#define GU_BUMP0 66
#define GU_BUMP1 74
#define BAL_UP 1
#define SPARSE0 81
#define SPARSE_STEP 4
#define CNT0 9
#define CNT1 81
#define GU_PROMO CU_TENSOR_MAP_L2_PROMOTION_L2_128B
#define GU_ROW(kap, j) ((kap) * 128 + (j) * 32)
#define H_DELAY 600
#define Q_DELAY 300
#define START_COUNT 1
#define POLL_NS 1500
constexpr int HALF_BYTES = 16384;
constexpr int STAGE_BYTES = 2 * HALF_BYTES;
constexpr int SMALL_BYTES = 14336;
constexpr int RG = 8;
constexpr int FF_G = D_FF / (NCTA / RG);
constexpr int NTHREADS = 320;

constexpr int MRG_HS = 132;
constexpr int MRG_WS = 8 * MRG_HS;

constexpr int OFF_MRG = STAGES * STAGE_BYTES;
constexpr int OFF_XN = OFF_MRG + 8 * MRG_WS * 4;
constexpr int OFF_XB = OFF_XN + 4096;
constexpr int OFF_Q = OFF_XB + 2048;
constexpr int OFF_REDQ = OFF_Q + 2048;
constexpr int OFF_REDG = OFF_REDQ + 1024;
constexpr int OFF_MS = OFF_REDG + 4 * 448 * 4;
constexpr int OFF_LS = OFF_MS + 256;
constexpr int OFF_LN = OFF_LS + 256;
constexpr int OFF_VEC = OFF_LN + 64;
constexpr int OFF_TAB = OFF_VEC + 1024;
constexpr int OFF_BAR = OFF_TAB + 2 * N_STEPS * 16;
constexpr int N_BARS = 3 * STAGES + 2;
constexpr int SMEM_USED = OFF_BAR + N_BARS * 8;
constexpr int SMEM_BYTES = SMEM_USED + 1024;

constexpr int P_REC = 40;
constexpr int BOX_O = CPG * P_REC;
constexpr int BOX_WORDS = BOX_O + 16 * 8;
constexpr int OUT_O = 2 * FF_G;
constexpr int OUT_WORDS = OUT_O + 32;
constexpr uint32_t TAG_MASK = 15u;
constexpr unsigned SPIN_LIMIT = 1u << 22;

constexpr float LOG2E = 1.4426950408889634f;
constexpr float SM_SCALE = 0.08838834764831845f;

__device__ unsigned int g_epoch;
__device__ __align__(128) unsigned int g_count;
__device__ __align__(128) unsigned int g_counts[8 * 32];
__device__ __align__(128) unsigned long long g_qbox[QCOLS / 2];
__device__ __align__(128) uint32_t g_inbox[NCTA * BOX_WORDS];
__device__ __align__(128) uint32_t g_outbox[NCTA * OUT_WORDS];
#define PROF(i) do { } while (0)
#define LAND(i) do { } while (0)
#define GT(i) do { } while (0)

__device__ __forceinline__ uint32_t smem_u32(const void* p) { return (uint32_t)__cvta_generic_to_shared(p); }
__device__ __forceinline__ void mbar_init(uint32_t a, uint32_t c) {
    asm volatile("mbarrier.init.shared::cta.b64 [%0], %1;" ::"r"(a), "r"(c) : "memory");
}
__device__ __forceinline__ void mbar_expect_tx(uint32_t a, uint32_t bytes) {
    asm volatile("mbarrier.arrive.expect_tx.shared::cta.b64 _, [%0], %1;" ::"r"(a), "r"(bytes) : "memory");
}
__device__ __forceinline__ void mbar_arrive(uint32_t a) {
    asm volatile("mbarrier.arrive.shared::cta.b64 _, [%0];" ::"r"(a) : "memory");
}
__device__ __forceinline__ bool mbar_try(uint32_t a, uint32_t parity) {
    uint32_t ok;
    asm volatile("{\n.reg .pred p;\nmbarrier.try_wait.parity.shared::cta.b64 p, [%1], %2;\nselp.u32 %0, 1, 0, p;\n}"
                 : "=r"(ok) : "r"(a), "r"(parity) : "memory");
    return ok != 0;
}
__device__ __forceinline__ bool mbar_try_ns(uint32_t a, uint32_t parity, uint32_t ns) {
    uint32_t ok;
    asm volatile("{\n.reg .pred p;\nmbarrier.try_wait.parity.shared::cta.b64 p, [%1], %2, %3;\nselp.u32 %0, 1, 0, p;\n}"
                 : "=r"(ok) : "r"(a), "r"(parity), "r"(ns) : "memory");
    return ok != 0;
}
__device__ __forceinline__ void mbar_wait(uint32_t a, uint32_t parity) {
    unsigned n = 0;
    while (!mbar_try(a, parity)) {
        if (++n > SPIN_LIMIT) __trap();
    }
}
__device__ __forceinline__ void tma2d_plain(uint32_t dst, const CUtensorMap* tm, int c0, int c1, uint32_t bar) {
    asm volatile("cp.async.bulk.tensor.2d.shared::cluster.global.mbarrier::complete_tx::bytes [%0], [%1, {%3, %4}], [%2];"
                 ::"r"(dst), "l"(tm), "r"(bar), "r"(c0), "r"(c1) : "memory");
}
__device__ __forceinline__ void tma3d(uint32_t dst, const CUtensorMap* tm, int c0, int c1, int c2, uint32_t bar, uint64_t pol) {
    asm volatile("cp.async.bulk.tensor.3d.shared::cluster.global.mbarrier::complete_tx::bytes.L2::cache_hint [%0], [%1, {%3, %4, %5}], [%2], %6;"
                 ::"r"(dst), "l"(tm), "r"(bar), "r"(c0), "r"(c1), "r"(c2), "l"(pol) : "memory");
}
__device__ __forceinline__ void prefetch_tmap(const CUtensorMap* tm) {
    asm volatile("prefetch.tensormap [%0];" ::"l"(tm) : "memory");
}
__device__ __forceinline__ void cons_sync() { asm volatile("bar.sync 1, 256;" ::: "memory"); }

__device__ __forceinline__ uint4 lds128(uint32_t a) {
    uint4 v;
    asm volatile("ld.shared.v4.u32 {%0, %1, %2, %3}, [%4];" : "=r"(v.x), "=r"(v.y), "=r"(v.z), "=r"(v.w) : "r"(a) : "memory");
    return v;
}
__device__ __forceinline__ void ldsm4(uint32_t a, uint32_t& r0, uint32_t& r1, uint32_t& r2, uint32_t& r3) {
    asm volatile("ldmatrix.sync.aligned.m8n8.x4.shared.b16 {%0, %1, %2, %3}, [%4];"
                 : "=r"(r0), "=r"(r1), "=r"(r2), "=r"(r3) : "r"(a));
}
__device__ __forceinline__ void ldsm4t(uint32_t a, uint32_t& r0, uint32_t& r1, uint32_t& r2, uint32_t& r3) {
    asm volatile("ldmatrix.sync.aligned.m8n8.x4.trans.shared.b16 {%0, %1, %2, %3}, [%4];"
                 : "=r"(r0), "=r"(r1), "=r"(r2), "=r"(r3) : "r"(a));
}
__device__ __forceinline__ void mma16816(float (&c)[4], uint32_t a0, uint32_t a1, uint32_t a2, uint32_t a3,
                                         uint32_t b0, uint32_t b1) {
    asm volatile("mma.sync.aligned.m16n8k16.row.col.f32.bf16.bf16.f32 {%0, %1, %2, %3}, {%4, %5, %6, %7}, {%8, %9}, {%0, %1, %2, %3};"
                 : "+f"(c[0]), "+f"(c[1]), "+f"(c[2]), "+f"(c[3])
                 : "r"(a0), "r"(a1), "r"(a2), "r"(a3), "r"(b0), "r"(b1));
}
__device__ __forceinline__ uint32_t movm_t(uint32_t a) {
    uint32_t d;
    asm volatile("movmatrix.sync.aligned.m8n8.trans.b16 %0, %1;" : "=r"(d) : "r"(a));
    return d;
}
__device__ __forceinline__ uint32_t pack_bf16(float lo, float hi) {
    uint32_t r;
    asm("cvt.rn.bf16x2.f32 %0, %1, %2;" : "=r"(r) : "f"(hi), "f"(lo));
    return r;
}
__device__ __forceinline__ float bf_lo(uint32_t v) { return __uint_as_float(v << 16); }
__device__ __forceinline__ float bf_hi(uint32_t v) { return __uint_as_float(v & 0xffff0000u); }
__device__ __forceinline__ float rbf(float x) { return __bfloat162float(__float2bfloat16_rn(x)); }
__device__ __forceinline__ float ex2(float x) {
    float y;
    asm("ex2.approx.ftz.f32 %0, %1;" : "=f"(y) : "f"(x));
    return y;
}
__device__ __forceinline__ void box_st1(unsigned long long* p, uint32_t payload, uint32_t epoch) {
    asm volatile("st.relaxed.gpu.global.b64 [%0], %1;" ::"l"(p), "l"(((unsigned long long)epoch << 32) | payload) : "memory");
}
__device__ __forceinline__ void box_ld2(const unsigned long long* p, unsigned long long& a, unsigned long long& b) {
    asm volatile("ld.relaxed.gpu.global.v2.b64 {%0, %1}, [%2];" : "=l"(a), "=l"(b) : "l"(p) : "memory");
}
__device__ __forceinline__ uint32_t pay(float v, uint32_t tag) { return (__float_as_uint(v) & ~TAG_MASK) | tag; }
__device__ __forceinline__ float val(uint32_t w) { return __uint_as_float(w & ~TAG_MASK); }
__device__ __forceinline__ bool tagged4(const uint4& v, uint32_t tag) {
    return (((v.x ^ tag) | (v.y ^ tag) | (v.z ^ tag) | (v.w ^ tag)) & TAG_MASK) == 0;
}
__device__ __forceinline__ void in_st1(uint32_t* p, uint32_t a) {
    asm volatile("st.relaxed.gpu.global.b32 [%0], %1;" ::"l"(p), "r"(a) : "memory");
}
__device__ __forceinline__ void in_st4(uint32_t* p, uint32_t a, uint32_t b, uint32_t c, uint32_t d) {
    asm volatile("st.relaxed.gpu.global.v4.b32 [%0], {%1, %2, %3, %4};" ::"l"(p), "r"(a), "r"(b), "r"(c), "r"(d) : "memory");
}
__device__ __forceinline__ uint4 in_ld4(const uint32_t* p) {
    uint4 v;
    asm volatile("ld.relaxed.gpu.global.v4.b32 {%0, %1, %2, %3}, [%4];" : "=r"(v.x), "=r"(v.y), "=r"(v.z), "=r"(v.w) : "l"(p) : "memory");
    return v;
}
__device__ __forceinline__ uint32_t in_ld1(const uint32_t* p) {
    uint32_t v;
    asm volatile("ld.relaxed.gpu.global.b32 %0, [%1];" : "=r"(v) : "l"(p) : "memory");
    return v;
}
__device__ __forceinline__ void fma8(float (&acc)[8], const uint4& w, float x) {
    acc[0] = fmaf(x, bf_lo(w.x), acc[0]); acc[1] = fmaf(x, bf_hi(w.x), acc[1]);
    acc[2] = fmaf(x, bf_lo(w.y), acc[2]); acc[3] = fmaf(x, bf_hi(w.y), acc[3]);
    acc[4] = fmaf(x, bf_lo(w.z), acc[4]); acc[5] = fmaf(x, bf_hi(w.z), acc[5]);
    acc[6] = fmaf(x, bf_lo(w.w), acc[6]); acc[7] = fmaf(x, bf_hi(w.w), acc[7]);
}
__device__ __forceinline__ void red_quads(float (&acc)[8]) {
#pragma unroll
    for (int i = 0; i < 8; i++) {
        acc[i] += __shfl_xor_sync(0xffffffffu, acc[i], 4);
        acc[i] += __shfl_xor_sync(0xffffffffu, acc[i], 8);
        acc[i] += __shfl_xor_sync(0xffffffffu, acc[i], 16);
    }
}
__device__ __forceinline__ float warp_sum(float v) {
#pragma unroll
    for (int o = 16; o > 0; o >>= 1) v += __shfl_xor_sync(0xffffffffu, v, o);
    return v;
}

__device__ __forceinline__ int vec_pos(int step, int e) {
    return (step * 4 + ((e >> 1) & 3)) * 32 + (e >> 4) * 4 + ((e >> 3) & 1) * 2 + (e & 1);
}
template <int W>
__device__ __forceinline__ void fold(float (&v)[32], int lane) {
    const bool up = lane & W;
#pragma unroll
    for (int i = 0; i < W; i++) {
        const float keep = up ? v[W + i] : v[i], send = up ? v[i] : v[W + i];
        v[i] = keep + __shfl_xor_sync(0xffffffffu, send, W);
    }
}

struct Maps { CUtensorMap k, v, q, g, u, d, o; };

__global__ void __launch_bounds__(NTHREADS, 1)
fused_decode_kernel(const __grid_constant__ Maps tm, const __nv_bfloat16* __restrict__ x,
                    const __nv_bfloat16* __restrict__ wq,
                    __nv_bfloat16* __restrict__ out) {
    extern __shared__ unsigned char smem_raw[];
    unsigned char* smem = smem_raw + ((1024u - (smem_u32(smem_raw) & 1023u)) & 1023u);
    const uint32_t sbase = smem_u32(smem);
    const uint32_t bar_fullA = sbase + OFF_BAR;
    const uint32_t bar_fullB = bar_fullA + 8 * STAGES;
    const uint32_t bar_empty = bar_fullB + 8 * STAGES;
    const uint32_t bar_kv = bar_empty + 8 * STAGES;
    const uint32_t bar_pub = bar_kv + 8;

    const int tid = threadIdx.x, warp = tid >> 5, lane = tid & 31;
    const int cta = blockIdx.x, grp = cta / CPG, gj = cta % CPG;
    const int rho = cta / RG, kap = cta % RG;
#define START_COND (tid == 256)
    if (START_COND) {
#pragma unroll
        for (int v = 0; v < 4; v++) {
            const uint32_t bar = ((v & 1) ? bar_fullB : bar_fullA) + 8 * (v >> 1);
            mbar_init(bar, 1);
            mbar_expect_tx(bar, HALF_BYTES);
            tma2d_plain(sbase + v * HALF_BYTES, &tm.q, cta * 32, v * 256, bar);
        }
        PROF(14);
    }
    uint32_t epoch_raw;
    asm volatile("ld.relaxed.gpu.global.u32 %0, [%1];" : "=r"(epoch_raw) : "l"(&g_epoch) : "memory");
    uint32_t* const inbox = &g_inbox[cta * BOX_WORDS];

    if (warp < 8) {
    float* xn = reinterpret_cast<float*>(smem + OFF_XN);
    const int g = lane >> 2, t = lane & 3;
    uint2 xraw;
    asm volatile("ld.global.nc.v2.u32 {%0, %1}, [%2];" : "=r"(xraw.x), "=r"(xraw.y) : "l"(x + tid * 4));
    const uint32_t epoch = epoch_raw + 1, tag = epoch & TAG_MASK;
    {
        float* ln = reinterpret_cast<float*>(smem + OFF_LN);
        const float x0 = bf_lo(xraw.x), x1 = bf_hi(xraw.x), x2 = bf_lo(xraw.y), x3 = bf_hi(xraw.y);
        float s = warp_sum((x0 + x1) + (x2 + x3));
        if (lane == 0) ln[warp] = s;
        asm volatile("bar.sync 2, 320;" ::: "memory");
        float tot = 0.f;
#pragma unroll
        for (int i = 0; i < 8; i++) tot += ln[i];
        const float mean = tot * (1.0f / D_MODEL);
        const float d0 = x0 - mean, d1 = x1 - mean, d2 = x2 - mean, d3 = x3 - mean;
        float v = warp_sum((d0 * d0 + d1 * d1) + (d2 * d2 + d3 * d3));
        if (lane == 0) ln[8 + warp] = v;
        cons_sync();
        float vt = 0.f;
#pragma unroll
        for (int i = 0; i < 8; i++) vt += ln[8 + i];
        const float mb = rbf(mean);
        const float sd = rbf(__fsqrt_rn(rbf(rbf(vt * (1.0f / D_MODEL)) + 1e-5f)));
        float4 o;
        o.x = rbf(__fdiv_rn(rbf(x0 - mb), sd));
        o.y = rbf(__fdiv_rn(rbf(x1 - mb), sd));
        o.z = rbf(__fdiv_rn(rbf(x2 - mb), sd));
        o.w = rbf(__fdiv_rn(rbf(x3 - mb), sd));
        reinterpret_cast<float4*>(xn)[tid] = o;
        reinterpret_cast<uint2*>(smem + OFF_XB)[tid] = make_uint2(pack_bf16(o.x, o.y), pack_bf16(o.z, o.w));
        cons_sync();
    }
    const int half = warp >> 2;
    const int gt = tid & 127;
    uint32_t qf[8][2];
    {
        float acc[8] = {0.f, 0.f, 0.f, 0.f, 0.f, 0.f, 0.f, 0.f};
        const uint32_t a = sbase + half * STAGE_BYTES + gt * 16;
        const float* xr = xn + half * 512 + (gt >> 2);
        mbar_wait(bar_fullA + 8 * half, 0);
#pragma unroll
        for (int i = 0; i < 8; i++) fma8(acc, lds128(a + i * 2048), xr[32 * i]);
        mbar_wait(bar_fullB + 8 * half, 0);
#pragma unroll
        for (int i = 0; i < 8; i++) fma8(acc, lds128(a + HALF_BYTES + i * 2048), xr[256 + 32 * i]);
        __syncwarp();
        if (lane == 0) mbar_arrive(bar_empty + 8 * half);
        red_quads(acc);
        float* rq = reinterpret_cast<float*>(smem + OFF_REDQ);
        if (lane < 4) {
            reinterpret_cast<float4*>(rq + warp * 32 + lane * 8)[0] = make_float4(acc[0], acc[1], acc[2], acc[3]);
            reinterpret_cast<float4*>(rq + warp * 32 + lane * 8)[1] = make_float4(acc[4], acc[5], acc[6], acc[7]);
        }
        cons_sync();
        if (tid < 16) {
            float qa = 0.f, qb = 0.f;
#pragma unroll
            for (int w = 0; w < 8; w++) { qa += rq[w * 32 + 2 * tid]; qb += rq[w * 32 + 2 * tid + 1]; }
            box_st1(&g_qbox[cta * 16 + tid], pack_bf16(qa, qb), epoch);
        }
        const unsigned long long* src = &g_qbox[grp * 512 + 2 * tid];
        unsigned long long qa, qb;
        unsigned n = 0;
        __nanosleep(Q_DELAY);
        while (true) {
            box_ld2(src, qa, qb);
            if ((uint32_t)(qa >> 32) == epoch && (uint32_t)(qb >> 32) == epoch) break;
            if (++n > SPIN_LIMIT) __trap();
            __nanosleep(100);
        }
        uint32_t* qs = reinterpret_cast<uint32_t*>(smem + OFF_Q);
        reinterpret_cast<uint2*>(qs)[tid] = make_uint2((uint32_t)qa, (uint32_t)qb);
        cons_sync();
#pragma unroll
        for (int ks = 0; ks < 8; ks++) {
            qf[ks][0] = qs[g * 64 + ks * 8 + t];
            qf[ks][1] = qs[g * 64 + ks * 8 + 4 + t];
        }
    }
    if (tid == 0) PROF(5);

    {
        float o[8][4];
#pragma unroll
        for (int i = 0; i < 8; i++) o[i][0] = o[i][1] = o[i][2] = o[i][3] = 0.f;
        float m0 = -INFINITY, m1 = -INFINITY, l0 = 0.f, l1 = 0.f;
        const int kw = (warp & 3) * 16, r7 = lane & 7, mi = lane >> 3;
        const uint32_t k_row = (kw + r7 + 8 * (mi & 1)) * 128;
        const uint32_t v_row = HALF_BYTES + (kw + r7 + 8 * (mi >> 1)) * 128;
        uint32_t k_off[4], v_off[4];
#pragma unroll
        for (int j = 0; j < 4; j++) {
            k_off[j] = k_row + (((2 * j + (mi >> 1)) ^ r7) << 4);
            v_off[j] = v_row + (((2 * j + (mi & 1)) ^ r7) << 4);
        }
        for (int n = KV0 + half; n < GU0; n += 2) {
            const int s = n % STAGES;
            const uint32_t ph = (n / STAGES) & 1;
            const uint32_t base = sbase + s * STAGE_BYTES;
            float sa[4] = {0.f, 0.f, 0.f, 0.f}, sb[4] = {0.f, 0.f, 0.f, 0.f};
            mbar_wait(bar_fullA + 8 * s, ph);
#pragma unroll
            for (int j = 0; j < 4; j++) {
                uint32_t a0, a1, a2, a3, c0, c1, c2, c3;
                ldsm4(base + k_off[j], a0, a1, a2, a3);
                ldsm4(base + k_off[j] + 8192, c0, c1, c2, c3);
                mma16816(sa, a0, a1, a2, a3, qf[j][0], qf[j][1]);
                mma16816(sb, c0, c1, c2, c3, qf[4 + j][0], qf[4 + j][1]);
            }
            const uint32_t r01 = pack_bf16(sa[0] + sb[0], sa[1] + sb[1]);
            const uint32_t r23 = pack_bf16(sa[2] + sb[2], sa[3] + sb[3]);
            const uint32_t u01 = pack_bf16(bf_lo(r01) * SM_SCALE, bf_hi(r01) * SM_SCALE);
            const uint32_t u23 = pack_bf16(bf_lo(r23) * SM_SCALE, bf_hi(r23) * SM_SCALE);
            const float s0 = bf_lo(u01), s1 = bf_hi(u01), s2 = bf_lo(u23), s3 = bf_hi(u23);
            float t0 = fmaxf(s0, s2), t1 = fmaxf(s1, s3);
#pragma unroll
            for (int sh = 4; sh <= 16; sh <<= 1) {
                t0 = fmaxf(t0, __shfl_xor_sync(0xffffffffu, t0, sh));
                t1 = fmaxf(t1, __shfl_xor_sync(0xffffffffu, t1, sh));
            }
            if (__any_sync(0xffffffffu, t0 > m0 || t1 > m1)) {
                const float n0 = fmaxf(m0, t0), n1 = fmaxf(m1, t1);
                const float f0 = ex2((m0 - n0) * LOG2E), f1 = ex2((m1 - n1) * LOG2E);
                m0 = n0; m1 = n1;
                l0 *= f0; l1 *= f1;
#pragma unroll
                for (int i = 0; i < 8; i++) { o[i][0] *= f0; o[i][1] *= f1; o[i][2] *= f0; o[i][3] *= f1; }
            }
            const float p0 = ex2((s0 - m0) * LOG2E), p1 = ex2((s1 - m1) * LOG2E);
            const float p2 = ex2((s2 - m0) * LOG2E), p3 = ex2((s3 - m1) * LOG2E);
            l0 += p0 + p2;
            l1 += p1 + p3;
            const uint32_t b0 = movm_t(pack_bf16(p0, p1));
            const uint32_t b1 = movm_t(pack_bf16(p2, p3));
            mbar_wait(bar_fullB + 8 * s, ph);
#pragma unroll
            for (int j = 0; j < 4; j++) {
                uint32_t a0, a1, a2, a3, c0, c1, c2, c3;
                ldsm4t(base + v_off[j], a0, a1, a2, a3);
                ldsm4t(base + v_off[j] + 8192, c0, c1, c2, c3);
                mma16816(o[j], a0, a1, a2, a3, b0, b1);
                mma16816(o[4 + j], c0, c1, c2, c3, b0, b1);
            }
            __syncwarp();
            if (lane == 0) mbar_arrive(bar_empty + 8 * s);
        }
        if (tid == 0) PROF(6);

        float* ms = reinterpret_cast<float*>(smem + OFF_MS);
        float* ls = reinterpret_cast<float*>(smem + OFF_LS);
        float* mrg = reinterpret_cast<float*>(smem + OFF_MRG);
        if (g == 0) reinterpret_cast<float2*>(ms + warp * 8)[t] = make_float2(m0, m1);
#pragma unroll
        for (int sh = 4; sh <= 16; sh <<= 1) {
            l0 += __shfl_xor_sync(0xffffffffu, l0, sh);
            l1 += __shfl_xor_sync(0xffffffffu, l1, sh);
        }
        cons_sync();
        float M0 = -INFINITY, M1 = -INFINITY;
#pragma unroll
        for (int w = 0; w < 8; w++) {
            const float2 v = reinterpret_cast<const float2*>(ms + w * 8)[t];
            M0 = fmaxf(M0, v.x); M1 = fmaxf(M1, v.y);
        }
        const float f0 = ex2((m0 - M0) * LOG2E), f1 = ex2((m1 - M1) * LOG2E);
        if (g == 0) reinterpret_cast<float2*>(ls + warp * 8)[t] = make_float2(l0 * f0, l1 * f1);
        float* dst = mrg + warp * MRG_WS + 2 * t * MRG_HS + g;
#pragma unroll
        for (int i = 0; i < 8; i++) {
            dst[16 * i] = o[i][0] * f0;
            dst[16 * i + MRG_HS] = o[i][1] * f1;
            dst[16 * i + 8] = o[i][2] * f0;
            dst[16 * i + 8 + MRG_HS] = o[i][3] * f1;
        }
        cons_sync();
        float a0 = 0.f, a1 = 0.f, a2 = 0.f, a3 = 0.f, L = 0.f, M = -INFINITY;
#pragma unroll
        for (int w = 0; w < 8; w++) {
            const float4 u = *reinterpret_cast<const float4*>(mrg + w * MRG_WS + warp * MRG_HS + 4 * lane);
            a0 += u.x; a1 += u.y; a2 += u.z; a3 += u.w;
            L += ls[w * 8 + warp];
            M = fmaxf(M, ms[w * 8 + warp]);
        }
        uint32_t* pb = &g_inbox[(grp * CPG + warp * 4) * BOX_WORDS + gj * P_REC];
        in_st4(pb + (lane >> 3) * BOX_WORDS + (lane & 7) * 4, pay(a0, tag), pay(a1, tag), pay(a2, tag), pay(a3, tag));
        if (lane < 8)
            in_st4(pb + (lane >> 1) * BOX_WORDS + 32 + (lane & 1) * 4, pay(M, tag), pay(L, tag), pay(M, tag), pay(L, tag));
        __syncwarp();
        if (lane == 0) mbar_arrive(bar_kv);
    }
    if (tid == 0) PROF(7);

    {
        float cg[7][4], cu[7][4];
#pragma unroll
        for (int i = 0; i < 7; i++) {
            cg[i][0] = cg[i][1] = cg[i][2] = cg[i][3] = 0.f;
            cu[i][0] = cu[i][1] = cu[i][2] = cu[i][3] = 0.f;
        }
        const int ks = warp & 1, mg = (warp >> 1) & 1, mi = lane >> 3;
        const uint32_t a_off = (ks * 16 + (lane & 7) + 8 * (mi >> 1)) * (FF_G * 2) + (mg * 14 + (mi & 1)) * 16;
        const uint32_t* xb = reinterpret_cast<const uint32_t*>(smem + OFF_XB) + ks * 8 + t;
#pragma unroll
        for (int k = 0; k < 2; k++) {
            const int n = GU0 + 2 * k + half;
            const int s = n % STAGES;
            const uint32_t ph = (n / STAGES) & 1;
            const uint32_t a = sbase + s * STAGE_BYTES + a_off;
            const uint32_t b0 = xb[GU_ROW(kap, n - GU0) / 2], b1 = xb[GU_ROW(kap, n - GU0) / 2 + 4];
            mbar_wait(bar_fullA + 8 * s, ph);
#pragma unroll
            for (int i = 0; i < 7; i++) {
                uint32_t a0, a1, a2, a3;
                ldsm4t(a + i * 32, a0, a1, a2, a3);
                mma16816(cg[i], a0, a1, a2, a3, b0, b1);
            }
            mbar_wait(bar_fullB + 8 * s, ph);
#pragma unroll
            for (int i = 0; i < 7; i++) {
                uint32_t a0, a1, a2, a3;
                ldsm4t(a + HALF_BYTES + i * 32, a0, a1, a2, a3);
                mma16816(cu[i], a0, a1, a2, a3, b0, b1);
            }
            __syncwarp();
            if (lane == 0) mbar_arrive(bar_empty + 8 * s);
        }
        float* rg = reinterpret_cast<float*>(smem + OFF_REDG);
        if (t < 2) {
            float* dst = rg + (half * 2 + ks) * (2 * FF_G) + t * FF_G + mg * 112 + g;
#pragma unroll
            for (int i = 0; i < 7; i++) {
                dst[16 * i] = t ? cu[i][0] : cg[i][0];
                dst[16 * i + 8] = t ? cu[i][2] : cg[i][2];
            }
        }
        cons_sync();
        if (tid < 2 * FF_G / 4) {
            const float4* p = reinterpret_cast<const float4*>(rg) + tid;
            const float4 u0 = p[0], u1 = p[112], u2 = p[224], u3 = p[336];
            in_st4(&g_outbox[cta * OUT_WORDS + 4 * tid], pay((u0.x + u1.x) + (u2.x + u3.x), tag),
                   pay((u0.y + u1.y) + (u2.y + u3.y), tag), pay((u0.z + u1.z) + (u2.z + u3.z), tag),
                   pay((u0.w + u1.w) + (u2.w + u3.w), tag));
        }
    }
    if (tid == 0) PROF(4);

    {
        float c0[4] = {0.f, 0.f, 0.f, 0.f}, c1[4] = {0.f, 0.f, 0.f, 0.f};
        uint32_t* const dst = &g_inbox[((2 * warp + (t & 1)) * RG + kap) * BOX_WORDS + BOX_O + rho * 8 + g];
        const int mi = lane >> 3, r7 = lane & 7;
        const uint32_t l_off = r7 * 128 + (((2 * (warp & 3) + (mi & 1)) ^ r7) << 4) + (mi >> 1) * 1024;
        {
            const uint32_t* hb = &g_outbox[rho * RG * OUT_WORDS + min(tid, FF_G - 1)];
            const uint32_t* src = &g_outbox[(rho * RG + warp) * OUT_WORDS + OUT_O + lane];
            uint32_t gw[RG], uw[RG], w = tag ^ 1;
#pragma unroll
            for (int j = 0; j < RG; j++) gw[j] = uw[j] = w;
            unsigned n = 0;
            __nanosleep(H_DELAY);
            while (true) {
                uint32_t bad = 0;
                if ((w ^ tag) & TAG_MASK) { bad = 1; w = in_ld1(src); }
#pragma unroll
                for (int j = 0; j < RG; j++) {
                    if (((gw[j] ^ tag) | (uw[j] ^ tag)) & TAG_MASK) {
                        bad = 1;
                        gw[j] = in_ld1(hb + j * OUT_WORDS);
                        uw[j] = in_ld1(hb + j * OUT_WORDS + FF_G);
                    }
                }
                if (!bad) break;
                if (++n > SPIN_LIMIT) __trap();
            }
            if (tid == 0) PROF(2);
            reinterpret_cast<uint16_t*>(smem + OFF_VEC)[vec_pos(tid >> 7, tid & 127)] = (uint16_t)(w >> 16);
            float gsum = 0.f, usum = 0.f;
#pragma unroll
            for (int j = 0; j < RG; j++) { gsum += val(gw[j]); usum += val(uw[j]); }
            const float gb = rbf(gsum), ub = rbf(usum);
            const float inner = 0.7978845608028654f * (gb + 0.044715f * gb * gb * gb);
            const float ge = rbf(0.5f * gb * (1.0f + tanhf(inner)));
            const int hi = tid >= 112;
            if (tid < FF_G)
                reinterpret_cast<__nv_bfloat16*>(smem + OFF_VEC)[vec_pos(2 + hi, tid - hi * 112)] = __float2bfloat16_rn(ge * ub);
            cons_sync();
            if (tid == 0) PROF(13);
        }
#pragma unroll 1
        for (int k = 0; k < 4; k++) {
            const int st = WO0 + k, s = st % STAGES, G = k < 2 ? 8 : 7;
            const uint32_t ph = (st / STAGES) & 1;
            const uint32_t vk = sbase + OFF_VEC + (k * 4 + t) * 64;
            const uint4 b0 = lds128(vk), b1 = lds128(vk + 16), b2 = lds128(vk + 32), b3 = lds128(vk + 48);
            const uint32_t ua = sbase + s * STAGE_BYTES + (warp >> 2) * (G * 1024) + l_off;
            const uint32_t ub = ua + HALF_BYTES - G * 1024;
            uint32_t a0, a1, a2, a3;
            mbar_wait(bar_fullA + 8 * s, ph);
            ldsm4t(ua, a0, a1, a2, a3);        mma16816(c0, a0, a1, a2, a3, b0.x, b0.y);
            ldsm4t(ua + 2048, a0, a1, a2, a3); mma16816(c1, a0, a1, a2, a3, b0.z, b0.w);
            ldsm4t(ua + 4096, a0, a1, a2, a3); mma16816(c0, a0, a1, a2, a3, b1.x, b1.y);
            mbar_wait(bar_fullB + 8 * s, ph);
            if (k == 3 && tid == 0) PROF(9);
            if (k == 0 && tid == 0) PROF(3);
            ldsm4t((6 + (mi >> 1) >= G ? ub : ua) + 6144, a0, a1, a2, a3); mma16816(c1, a0, a1, a2, a3, b1.z, b1.w);
            ldsm4t(ub + 8192, a0, a1, a2, a3);  mma16816(c0, a0, a1, a2, a3, b2.x, b2.y);
            ldsm4t(ub + 10240, a0, a1, a2, a3); mma16816(c1, a0, a1, a2, a3, b2.z, b2.w);
            ldsm4t(ub + 12288, a0, a1, a2, a3); mma16816(c0, a0, a1, a2, a3, b3.x, b3.y);
            if (k < 2) { ldsm4t(ub + 14336, a0, a1, a2, a3); mma16816(c1, a0, a1, a2, a3, b3.z, b3.w); }
            if (k == 3 && t < 2) in_st1(dst, pay(t ? c0[2] + c1[2] : c0[0] + c1[0], tag));
        }
        if (tid == 0) PROF(10);
        __syncwarp();
        if (lane == 0) mbar_arrive(bar_pub);
    }
    } else if (warp == 9) {
        const uint32_t epoch = epoch_raw + 1, tag = epoch & TAG_MASK;
        const int ocol = kap * 128 + rho * 8 + (lane & 1) * 4 + (lane >> 4) * 2 + ((lane >> 3) & 1);
        const float xres = __bfloat162float(x[ocol]);
        {
            const uint32_t e = tag ^ 8u;
#pragma unroll
            for (int i = 0; i < 4; i++)
                if (i * 128 + lane * 4 < OUT_WORDS) in_st4(&g_outbox[cta * OUT_WORDS + i * 128 + lane * 4], e, e, e, e);
            if (lane < 16) box_st1(&g_qbox[cta * 16 + lane], 0, epoch_raw);
        }
        asm volatile("bar.sync 2, 320;" ::: "memory");
        unsigned n = 0;
        mbar_wait(bar_kv, 0);
        {
            const uint32_t* src = inbox + lane * P_REC;
            uint4 a[8], ml;
            while (true) {
                ml = in_ld4(src + 32);
                if (tagged4(ml, tag)) break;
                if (++n > SPIN_LIMIT) __trap();
                __nanosleep(PROBE_NS);
            }
            while (true) {
#pragma unroll
                for (int i = 0; i < 8; i++) a[i] = in_ld4(src + 4 * i);
                bool ok = true;
#pragma unroll
                for (int i = 0; i < 8; i++) ok = ok && tagged4(a[i], tag);
                if (ok) break;
                if (++n > SPIN_LIMIT) __trap();
                __nanosleep(300);
            }
            __syncwarp();
            const float m = val(ml.x);
            int key = __float_as_int(m);
            key = key >= 0 ? key : key ^ 0x7fffffff;
            key = __reduce_max_sync(0xffffffffu, key);
            key = key >= 0 ? key : key ^ 0x7fffffff;
            const float wgt = ex2((m - __int_as_float(key)) * LOG2E);
            const float L = warp_sum(val(ml.y) * wgt);
            float v[32];
#pragma unroll
            for (int i = 0; i < 8; i++) {
                v[4 * i] = val(a[i].x) * wgt; v[4 * i + 1] = val(a[i].y) * wgt;
                v[4 * i + 2] = val(a[i].z) * wgt; v[4 * i + 3] = val(a[i].w) * wgt;
            }
            fold<16>(v, lane); fold<8>(v, lane); fold<4>(v, lane); fold<2>(v, lane); fold<1>(v, lane);
            const uint32_t ob = pack_bf16(0.f, __fdiv_rn(v[0], L));
            in_st1(&g_outbox[cta * OUT_WORDS + OUT_O + lane], ob | tag);
            if (lane == 0) PROF(8);
        }
        const uint32_t* src = inbox + BOX_O + lane * 4;
#pragma unroll 1
        for (int pass = DRY0; pass < 2; pass++) {
            uint4 a = in_ld4(src);
            if (pass) {
                while (!tagged4(a, tag) && !mbar_try_ns(bar_pub, 0, POLL_NS)) {
                    a = in_ld4(src);
                    if (++n > SPIN_LIMIT) __trap();
                }
                while (!tagged4(a, tag)) {
                    a = in_ld4(src);
                    if (++n > SPIN_LIMIT) __trap();
                }
            }
            __syncwarp();
            const bool b4 = lane & 16, b3 = lane & 8;
            float v0 = (b4 ? val(a.z) : val(a.x)) + __shfl_xor_sync(0xffffffffu, b4 ? val(a.x) : val(a.z), 16);
            float v1 = (b4 ? val(a.w) : val(a.y)) + __shfl_xor_sync(0xffffffffu, b4 ? val(a.y) : val(a.w), 16);
            float r = (b3 ? v1 : v0) + __shfl_xor_sync(0xffffffffu, b3 ? v0 : v1, 8);
            r += __shfl_xor_sync(0xffffffffu, r, 4);
            r += __shfl_xor_sync(0xffffffffu, r, 2);
            if (pass && (lane & 6) == 0) out[ocol] = __float2bfloat16_rn(xres + r);
        }
        if (cta == 0 && lane == 0) g_epoch = epoch;
        if (lane == 0) { PROF(11); GT(1); }
    } else {
        const int key0 = grp * S_K + gj * TILE_KEYS;
        uint64_t pol;
        asm volatile("createpolicy.fractional.L2::evict_first.b64 %0, 1.0;" : "=l"(pol));
        int4* tab = reinterpret_cast<int4*>(smem + OFF_TAB);
        for (int v = 4 + lane; v < 2 * N_STEPS; v += 32) {
            const int n = v >> 1, hb = v & 1;
            int4 e;
            if (n < GU0) e = make_int4(hb | (HALF_BYTES << 8), 0, key0 + (n - KV0) * (CPG * TILE_KEYS), 0);
            else if (n < WO0) e = make_int4((3 + hb) | (SMALL_BYTES << 8), rho * FF_G, GU_ROW(kap, n - GU0), 0);
            else if (n < DN0) e = make_int4(6 | (HALF_BYTES << 8), 0, rho * 256 + (v - 2 * WO0) * 64, 2 * kap);
            else e = make_int4(5 | (SMALL_BYTES << 8), 0, rho * FF_G + (v - 2 * DN0) * 56, 2 * kap);
            tab[v] = e;
        }
        if (lane == 0) {
            PROF(0);
            GT(0);
#pragma unroll
            for (int s = 0; s < STAGES; s++) {
                if (s >= 2) {
                    mbar_init(bar_fullA + 8 * s, 1);
                    mbar_init(bar_fullB + 8 * s, 1);
                }
                mbar_init(bar_empty + 8 * s, 4);
            }
            mbar_init(bar_kv, V_PROBE >= 0 ? 9 : 8);
            mbar_init(bar_pub, 8);
            asm volatile("fence.mbarrier_init.release.cluster;" ::: "memory");
        } else if (lane < 7) {
            prefetch_tmap(&tm.k + (lane == 1 ? 0 : lane == 2 ? 1 : lane));
        }
        __syncwarp();
        asm volatile("bar.arrive 2, 320;" ::: "memory");
        if (lane == 0) {
            constexpr int N_COUNTS = (CNT1 - CNT0) / 2 + START_COUNT;
            if (START_COUNT) asm volatile("red.relaxed.gpu.global.add.u32 [%0], 1;" ::"l"(&g_count) : "memory");
            int landed = 0, next = CNT0, mine = NCTA / 2 + START_COUNT * NCTA, win = WIN;
            for (int v = 4; v < 2 * N_STEPS || next < CNT1; v++) {
                const bool go = v < 2 * N_STEPS;
                const int n = v >> 1, s = n % STAGES, hb = v & 1;
                const int4 e = tab[go ? v : 4];
                const uint32_t bar = (hb ? bar_fullB : bar_fullA) + 8 * s;
                if (go && !hb && n >= STAGES) mbar_wait(bar_empty + 8 * s, ((n / STAGES) & 1) ^ 1);
                while (landed <= v - win) {
                    const int wn = landed >> 1;
                    mbar_wait(((landed & 1) ? bar_fullB : bar_fullA) + 8 * (wn % STAGES), (wn / STAGES) & 1);
                    LAND(landed);
                    landed++;
                }
                if (go) {
                    mbar_expect_tx(bar, e.x >> 8);
                    tma3d(sbase + s * STAGE_BYTES + hb * HALF_BYTES, &tm.k + (e.x & 7), e.y, e.z, e.w, bar, pol);
                    if (v == 2 * GU0 - 1) PROF(1);
                    if (v == 2 * GU0 + V_PROBE) mbar_arrive(bar_kv);
                }
                if (landed > next && next < CNT1) {
                    const uint32_t seen = atomicAdd(&g_count, 1u) - epoch_raw * (uint32_t)(NCTA * N_COUNTS);
                    const int lead = mine - (int)seen;
                    win = lead > BAL_T ? WIN - 1 : (lead < -BAL_TL ? WIN + BAL_UP : WIN);
                    if (landed >= GU_BUMP0 && landed < GU_BUMP1) win++;
                    mine += NCTA;
                    next += 2;
                }
            }
            PROF(12);
        }
    }
}

typedef CUresult (*EncodeFn)(CUtensorMap*, CUtensorMapDataType, cuuint32_t, void*, const cuuint64_t*, const cuuint64_t*,
                             const cuuint32_t*, const cuuint32_t*, CUtensorMapInterleave, CUtensorMapSwizzle,
                             CUtensorMapL2promotion, CUtensorMapFloatOOBfill);

void map_blocks(EncodeFn enc, CUtensorMap* m, void* p, uint64_t rows, uint32_t row_elems, uint32_t box_rows) {
    const cuuint64_t gd[3] = {64, rows, row_elems / 64};
    const cuuint64_t gs[2] = {(cuuint64_t)row_elems * 2, 128};
    const cuuint32_t bd[3] = {64, box_rows, 2};
    const cuuint32_t es[3] = {1, 1, 1};
    enc(m, CU_TENSOR_MAP_DATA_TYPE_BFLOAT16, 3, p, gd, gs, bd, es, CU_TENSOR_MAP_INTERLEAVE_NONE,
        CU_TENSOR_MAP_SWIZZLE_128B, KV_PROMO, CU_TENSOR_MAP_FLOAT_OOB_FILL_NONE);
}
void map_cols(EncodeFn enc, CUtensorMap* m, void* p, int rank, uint64_t cols, uint32_t box_cols, uint32_t box_rows,
              CUtensorMapL2promotion promo) {
    const cuuint64_t gd[3] = {cols, D_MODEL, 1};
    const cuuint64_t gs[2] = {cols * 2, cols * 2 * D_MODEL};
    const cuuint32_t bd[3] = {box_cols, box_rows, 1};
    const cuuint32_t es[3] = {1, 1, 1};
    enc(m, CU_TENSOR_MAP_DATA_TYPE_BFLOAT16, rank, p, gd, gs, bd, es, CU_TENSOR_MAP_INTERLEAVE_NONE,
        CU_TENSOR_MAP_SWIZZLE_NONE, promo, CU_TENSOR_MAP_FLOAT_OOB_FILL_NONE);
}

}

extern "C" void kernel_launch(void* const* d_in, const int* in_sizes, int n_in, void* d_out, int out_size) {
    (void)in_sizes; (void)n_in; (void)out_size;
    static EncodeFn encode = nullptr;
    if (!encode) {
        void* fn = nullptr;
        cudaDriverEntryPointQueryResult qr;
        cudaGetDriverEntryPoint("cuTensorMapEncodeTiled", &fn, cudaEnableDefault, &qr);
        encode = (EncodeFn)fn;
        cudaFuncSetAttribute(fused_decode_kernel, cudaFuncAttributeMaxDynamicSharedMemorySize, SMEM_BYTES);
    }
    Maps tm;
    map_blocks(encode, &tm.k, d_in[1], (uint64_t)N_HKV * S_K, 128, TILE_KEYS);
    map_blocks(encode, &tm.v, d_in[2], (uint64_t)N_HKV * S_K, 128, TILE_KEYS);
    map_cols(encode, &tm.q, d_in[3], 2, QCOLS, 32, 256, CU_TENSOR_MAP_L2_PROMOTION_L2_128B);
    map_cols(encode, &tm.g, d_in[6], 3, D_FF, FF_G, 32, GU_PROMO);
    map_cols(encode, &tm.u, d_in[7], 3, D_FF, FF_G, 32, GU_PROMO);
    map_blocks(encode, &tm.d, d_in[8], D_FF, D_MODEL, 56);
    map_blocks(encode, &tm.o, d_in[4], QCOLS, D_MODEL, 64);
    fused_decode_kernel<<<NCTA, NTHREADS, SMEM_BYTES, cudaStreamPerThread>>>(
        tm, (const __nv_bfloat16*)d_in[0], (const __nv_bfloat16*)d_in[1],
        (__nv_bfloat16*)d_out);
}
```

```cpp
#include <cuda_runtime.h>
#include <cuda_bf16.h>
#include <cuda.h>
#include <stdint.h>

namespace {

constexpr int D_MODEL = 1024;
constexpr int N_HKV = 4;
constexpr int S_K = 65536;
constexpr int D_FF = 3584;
constexpr int QCOLS = 4096;

constexpr int NCTA = 128;
constexpr int CPG = 32;
constexpr int TILE_KEYS = 64;
constexpr int KV_TILES = S_K / CPG / TILE_KEYS;
constexpr int KV0 = 2;
constexpr int GU0 = KV0 + KV_TILES;
constexpr int WO0 = GU0 + 4;
constexpr int DN0 = WO0 + 2;
constexpr int N_STEPS = DN0 + 2;
constexpr int STAGES = 4;
constexpr int WIN = 3;
constexpr int LEAD_HI = 96, LEAD_END = 32, LEAD_LO = 32;
constexpr int CNT0 = 9, CNT1 = 81;
constexpr int WIDE0 = 2 * GU0 - 2, WIDE1 = 2 * WO0 - 2;
constexpr int V_COMBINE = 2 * GU0 + 6;
constexpr int HALF_BYTES = 16384;
constexpr int STAGE_BYTES = 2 * HALF_BYTES;
constexpr int SMALL_BYTES = 14336;
constexpr int RG = 8;
constexpr int FF_G = D_FF / (NCTA / RG);
constexpr int NTHREADS = 320;

constexpr int MRG_HS = 132;
constexpr int MRG_WS = 8 * MRG_HS;

constexpr int OFF_MRG = STAGES * STAGE_BYTES;
constexpr int OFF_XN = OFF_MRG + 8 * MRG_WS * 4;
constexpr int OFF_XB = OFF_XN + 4096;
constexpr int OFF_Q = OFF_XB + 2048;
constexpr int OFF_REDQ = OFF_Q + 2048;
constexpr int OFF_REDG = OFF_REDQ + 1024;
constexpr int OFF_MS = OFF_REDG + 4 * 448 * 4;
constexpr int OFF_LS = OFF_MS + 256;
constexpr int OFF_LN = OFF_LS + 256;
constexpr int OFF_VEC = OFF_LN + 64;
constexpr int OFF_TAB = OFF_VEC + 1024;
constexpr int OFF_BAR = OFF_TAB + 2 * N_STEPS * 16;
constexpr int N_BARS = 3 * STAGES + 2;
constexpr int SMEM_USED = OFF_BAR + N_BARS * 8;
constexpr int SMEM_BYTES = SMEM_USED + 1024;

constexpr int P_REC = 40;
constexpr int BOX_O = CPG * P_REC;
constexpr int BOX_WORDS = BOX_O + 16 * 8;
constexpr int OUT_O = 2 * FF_G;
constexpr int OUT_WORDS = OUT_O + 32;
constexpr uint32_t TAG_MASK = 15u;
constexpr unsigned SPIN_LIMIT = 1u << 22;

constexpr float LOG2E = 1.4426950408889634f;
constexpr float SM_SCALE = 0.08838834764831845f;

__device__ unsigned int g_epoch;
__device__ __align__(128) unsigned int g_count;
__device__ __align__(128) unsigned long long g_qbox[QCOLS / 2];
__device__ __align__(128) uint32_t g_inbox[NCTA * BOX_WORDS];
__device__ __align__(128) uint32_t g_outbox[NCTA * OUT_WORDS];

__device__ __forceinline__ uint32_t smem_u32(const void* p) { return (uint32_t)__cvta_generic_to_shared(p); }
__device__ __forceinline__ void mbar_init(uint32_t a, uint32_t c) {
    asm volatile("mbarrier.init.shared::cta.b64 [%0], %1;" ::"r"(a), "r"(c) : "memory");
}
__device__ __forceinline__ void mbar_expect_tx(uint32_t a, uint32_t bytes) {
    asm volatile("mbarrier.arrive.expect_tx.shared::cta.b64 _, [%0], %1;" ::"r"(a), "r"(bytes) : "memory");
}
__device__ __forceinline__ void mbar_arrive(uint32_t a) {
    asm volatile("mbarrier.arrive.shared::cta.b64 _, [%0];" ::"r"(a) : "memory");
}
__device__ __forceinline__ bool mbar_try(uint32_t a, uint32_t parity) {
    uint32_t ok;
    asm volatile("{\n.reg .pred p;\nmbarrier.try_wait.parity.shared::cta.b64 p, [%1], %2;\nselp.u32 %0, 1, 0, p;\n}"
                 : "=r"(ok) : "r"(a), "r"(parity) : "memory");
    return ok != 0;
}
__device__ __forceinline__ bool mbar_try_ns(uint32_t a, uint32_t parity, uint32_t ns) {
    uint32_t ok;
    asm volatile("{\n.reg .pred p;\nmbarrier.try_wait.parity.shared::cta.b64 p, [%1], %2, %3;\nselp.u32 %0, 1, 0, p;\n}"
                 : "=r"(ok) : "r"(a), "r"(parity), "r"(ns) : "memory");
    return ok != 0;
}
__device__ __forceinline__ void mbar_wait(uint32_t a, uint32_t parity) {
    unsigned n = 0;
    while (!mbar_try(a, parity)) {
        if (++n > SPIN_LIMIT) __trap();
    }
}
__device__ __forceinline__ void tma2d_plain(uint32_t dst, const CUtensorMap* tm, int c0, int c1, uint32_t bar) {
    asm volatile("cp.async.bulk.tensor.2d.shared::cluster.global.mbarrier::complete_tx::bytes [%0], [%1, {%3, %4}], [%2];"
                 ::"r"(dst), "l"(tm), "r"(bar), "r"(c0), "r"(c1) : "memory");
}
__device__ __forceinline__ void tma3d(uint32_t dst, const CUtensorMap* tm, int c0, int c1, int c2, uint32_t bar, uint64_t pol) {
    asm volatile("cp.async.bulk.tensor.3d.shared::cluster.global.mbarrier::complete_tx::bytes.L2::cache_hint [%0], [%1, {%3, %4, %5}], [%2], %6;"
                 ::"r"(dst), "l"(tm), "r"(bar), "r"(c0), "r"(c1), "r"(c2), "l"(pol) : "memory");
}
__device__ __forceinline__ void prefetch_tmap(const CUtensorMap* tm) {
    asm volatile("prefetch.tensormap [%0];" ::"l"(tm) : "memory");
}
__device__ __forceinline__ void cons_sync() { asm volatile("bar.sync 1, 256;" ::: "memory"); }

__device__ __forceinline__ uint4 lds128(uint32_t a) {
    uint4 v;
    asm volatile("ld.shared.v4.u32 {%0, %1, %2, %3}, [%4];" : "=r"(v.x), "=r"(v.y), "=r"(v.z), "=r"(v.w) : "r"(a) : "memory");
    return v;
}
__device__ __forceinline__ void ldsm4(uint32_t a, uint32_t& r0, uint32_t& r1, uint32_t& r2, uint32_t& r3) {
    asm volatile("ldmatrix.sync.aligned.m8n8.x4.shared.b16 {%0, %1, %2, %3}, [%4];"
                 : "=r"(r0), "=r"(r1), "=r"(r2), "=r"(r3) : "r"(a));
}
__device__ __forceinline__ void ldsm4t(uint32_t a, uint32_t& r0, uint32_t& r1, uint32_t& r2, uint32_t& r3) {
    asm volatile("ldmatrix.sync.aligned.m8n8.x4.trans.shared.b16 {%0, %1, %2, %3}, [%4];"
                 : "=r"(r0), "=r"(r1), "=r"(r2), "=r"(r3) : "r"(a));
}
__device__ __forceinline__ void mma16816(float (&c)[4], uint32_t a0, uint32_t a1, uint32_t a2, uint32_t a3,
                                         uint32_t b0, uint32_t b1) {
    asm volatile("mma.sync.aligned.m16n8k16.row.col.f32.bf16.bf16.f32 {%0, %1, %2, %3}, {%4, %5, %6, %7}, {%8, %9}, {%0, %1, %2, %3};"
                 : "+f"(c[0]), "+f"(c[1]), "+f"(c[2]), "+f"(c[3])
                 : "r"(a0), "r"(a1), "r"(a2), "r"(a3), "r"(b0), "r"(b1));
}
__device__ __forceinline__ uint32_t movm_t(uint32_t a) {
    uint32_t d;
    asm volatile("movmatrix.sync.aligned.m8n8.trans.b16 %0, %1;" : "=r"(d) : "r"(a));
    return d;
}
__device__ __forceinline__ uint32_t pack_bf16(float lo, float hi) {
    uint32_t r;
    asm("cvt.rn.bf16x2.f32 %0, %1, %2;" : "=r"(r) : "f"(hi), "f"(lo));
    return r;
}
__device__ __forceinline__ float bf_lo(uint32_t v) { return __uint_as_float(v << 16); }
__device__ __forceinline__ float bf_hi(uint32_t v) { return __uint_as_float(v & 0xffff0000u); }
__device__ __forceinline__ float rbf(float x) { return __bfloat162float(__float2bfloat16_rn(x)); }
__device__ __forceinline__ float ex2(float x) {
    float y;
    asm("ex2.approx.ftz.f32 %0, %1;" : "=f"(y) : "f"(x));
    return y;
}
__device__ __forceinline__ void box_st1(unsigned long long* p, uint32_t payload, uint32_t epoch) {
    asm volatile("st.relaxed.gpu.global.b64 [%0], %1;" ::"l"(p), "l"(((unsigned long long)epoch << 32) | payload) : "memory");
}
__device__ __forceinline__ void box_ld2(const unsigned long long* p, unsigned long long& a, unsigned long long& b) {
    asm volatile("ld.relaxed.gpu.global.v2.b64 {%0, %1}, [%2];" : "=l"(a), "=l"(b) : "l"(p) : "memory");
}
__device__ __forceinline__ uint32_t pay(float v, uint32_t tag) { return (__float_as_uint(v) & ~TAG_MASK) | tag; }
__device__ __forceinline__ float val(uint32_t w) { return __uint_as_float(w & ~TAG_MASK); }
__device__ __forceinline__ bool tagged4(const uint4& v, uint32_t tag) {
    return (((v.x ^ tag) | (v.y ^ tag) | (v.z ^ tag) | (v.w ^ tag)) & TAG_MASK) == 0;
}
__device__ __forceinline__ void in_st1(uint32_t* p, uint32_t a) {
    asm volatile("st.relaxed.gpu.global.b32 [%0], %1;" ::"l"(p), "r"(a) : "memory");
}
__device__ __forceinline__ void in_st4(uint32_t* p, uint32_t a, uint32_t b, uint32_t c, uint32_t d) {
    asm volatile("st.relaxed.gpu.global.v4.b32 [%0], {%1, %2, %3, %4};" ::"l"(p), "r"(a), "r"(b), "r"(c), "r"(d) : "memory");
}
__device__ __forceinline__ uint4 in_ld4(const uint32_t* p) {
    uint4 v;
    asm volatile("ld.relaxed.gpu.global.v4.b32 {%0, %1, %2, %3}, [%4];" : "=r"(v.x), "=r"(v.y), "=r"(v.z), "=r"(v.w) : "l"(p) : "memory");
    return v;
}
__device__ __forceinline__ uint32_t in_ld1(const uint32_t* p) {
    uint32_t v;
    asm volatile("ld.relaxed.gpu.global.b32 %0, [%1];" : "=r"(v) : "l"(p) : "memory");
    return v;
}
__device__ __forceinline__ void fma8(float (&acc)[8], const uint4& w, float x) {
    acc[0] = fmaf(x, bf_lo(w.x), acc[0]); acc[1] = fmaf(x, bf_hi(w.x), acc[1]);
    acc[2] = fmaf(x, bf_lo(w.y), acc[2]); acc[3] = fmaf(x, bf_hi(w.y), acc[3]);
    acc[4] = fmaf(x, bf_lo(w.z), acc[4]); acc[5] = fmaf(x, bf_hi(w.z), acc[5]);
    acc[6] = fmaf(x, bf_lo(w.w), acc[6]); acc[7] = fmaf(x, bf_hi(w.w), acc[7]);
}
__device__ __forceinline__ void red_quads(float (&acc)[8]) {
#pragma unroll
    for (int i = 0; i < 8; i++) {
        acc[i] += __shfl_xor_sync(0xffffffffu, acc[i], 4);
        acc[i] += __shfl_xor_sync(0xffffffffu, acc[i], 8);
        acc[i] += __shfl_xor_sync(0xffffffffu, acc[i], 16);
    }
}
__device__ __forceinline__ float warp_sum(float v) {
#pragma unroll
    for (int o = 16; o > 0; o >>= 1) v += __shfl_xor_sync(0xffffffffu, v, o);
    return v;
}

__device__ __forceinline__ int vec_pos(int step, int e) {
    return (step * 4 + ((e >> 1) & 3)) * 32 + (e >> 4) * 4 + ((e >> 3) & 1) * 2 + (e & 1);
}
template <int W>
__device__ __forceinline__ void fold(float (&v)[32], int lane) {
    const bool up = lane & W;
#pragma unroll
    for (int i = 0; i < W; i++) {
        const float keep = up ? v[W + i] : v[i], send = up ? v[i] : v[W + i];
        v[i] = keep + __shfl_xor_sync(0xffffffffu, send, W);
    }
}

struct Maps { CUtensorMap k, v, q, g, u, d, o; };

__global__ void __launch_bounds__(NTHREADS, 1)
fused_decode_kernel(const __nv_bfloat16* __restrict__ kc, const __nv_bfloat16* __restrict__ x,
                    __nv_bfloat16* __restrict__ out, const __grid_constant__ Maps tm) {
    extern __shared__ unsigned char smem_raw[];
    unsigned char* smem = smem_raw + ((1024u - (smem_u32(smem_raw) & 1023u)) & 1023u);
    const uint32_t sbase = smem_u32(smem);
    const uint32_t bar_fullA = sbase + OFF_BAR;
    const uint32_t bar_fullB = bar_fullA + 8 * STAGES;
    const uint32_t bar_empty = bar_fullB + 8 * STAGES;
    const uint32_t bar_kv = bar_empty + 8 * STAGES;
    const uint32_t bar_pub = bar_kv + 8;

    const int tid = threadIdx.x, warp = tid >> 5, lane = tid & 31;
    const int cta = blockIdx.x, grp = cta / CPG, gj = cta % CPG;
    const int rho = cta / RG, kap = cta % RG;
    if (tid == 256) {
        asm volatile("cp.async.bulk.prefetch.L2.global [%0], 4096;" ::"l"(kc + (size_t)(grp * S_K + gj * TILE_KEYS) * 128) : "memory");
#pragma unroll
        for (int v = 0; v < 4; v++) mbar_init(((v & 1) ? bar_fullB : bar_fullA) + 8 * (v >> 1), 1);
        asm volatile("fence.proxy.async.shared::cta;" ::: "memory");
#pragma unroll
        for (int v = 0; v < 4; v++) {
            const uint32_t bar = ((v & 1) ? bar_fullB : bar_fullA) + 8 * (v >> 1);
            mbar_expect_tx(bar, HALF_BYTES);
            tma2d_plain(sbase + v * HALF_BYTES, &tm.q, cta * 32, v * 256, bar);
        }
    }
    uint32_t epoch_raw;
    asm volatile("ld.relaxed.gpu.global.u32 %0, [%1];" : "=r"(epoch_raw) : "l"(&g_epoch) : "memory");
    uint32_t* const inbox = &g_inbox[cta * BOX_WORDS];

    if (warp < 8) {
    float* xn = reinterpret_cast<float*>(smem + OFF_XN);
    const int g = lane >> 2, t = lane & 3;
    uint2 xraw;
    asm volatile("ld.global.nc.v2.u32 {%0, %1}, [%2];" : "=r"(xraw.x), "=r"(xraw.y) : "l"(x + tid * 4));
    const uint32_t epoch = epoch_raw + 1, tag = epoch & TAG_MASK;
    {
        float* ln = reinterpret_cast<float*>(smem + OFF_LN);
        const float x0 = bf_lo(xraw.x), x1 = bf_hi(xraw.x), x2 = bf_lo(xraw.y), x3 = bf_hi(xraw.y);
        float s = warp_sum((x0 + x1) + (x2 + x3));
        if (lane == 0) ln[warp] = s;
        asm volatile("bar.sync 2, 320;" ::: "memory");
        float tot = 0.f;
#pragma unroll
        for (int i = 0; i < 8; i++) tot += ln[i];
        const float mean = tot * (1.0f / D_MODEL);
        const float d0 = x0 - mean, d1 = x1 - mean, d2 = x2 - mean, d3 = x3 - mean;
        float v = warp_sum((d0 * d0 + d1 * d1) + (d2 * d2 + d3 * d3));
        if (lane == 0) ln[8 + warp] = v;
        cons_sync();
        float vt = 0.f;
#pragma unroll
        for (int i = 0; i < 8; i++) vt += ln[8 + i];
        const float mb = rbf(mean);
        const float sd = rbf(__fsqrt_rn(rbf(rbf(vt * (1.0f / D_MODEL)) + 1e-5f)));
        float4 o;
        o.x = rbf(__fdiv_rn(rbf(x0 - mb), sd));
        o.y = rbf(__fdiv_rn(rbf(x1 - mb), sd));
        o.z = rbf(__fdiv_rn(rbf(x2 - mb), sd));
        o.w = rbf(__fdiv_rn(rbf(x3 - mb), sd));
        reinterpret_cast<float4*>(xn)[tid] = o;
        reinterpret_cast<uint2*>(smem + OFF_XB)[tid] = make_uint2(pack_bf16(o.x, o.y), pack_bf16(o.z, o.w));
        cons_sync();
    }
    const int half = warp >> 2;
    const int gt = tid & 127;
    uint32_t qf[8][2];
    {
        float acc[8] = {0.f, 0.f, 0.f, 0.f, 0.f, 0.f, 0.f, 0.f};
        const uint32_t a = sbase + half * STAGE_BYTES + gt * 16;
        const float* xr = xn + half * 512 + (gt >> 2);
        mbar_wait(bar_fullA + 8 * half, 0);
#pragma unroll
        for (int i = 0; i < 8; i++) fma8(acc, lds128(a + i * 2048), xr[32 * i]);
        mbar_wait(bar_fullB + 8 * half, 0);
#pragma unroll
        for (int i = 0; i < 8; i++) fma8(acc, lds128(a + HALF_BYTES + i * 2048), xr[256 + 32 * i]);
        __syncwarp();
        if (lane == 0) mbar_arrive(bar_empty + 8 * half);
        red_quads(acc);
        float* rq = reinterpret_cast<float*>(smem + OFF_REDQ);
        if (lane < 4) {
            reinterpret_cast<float4*>(rq + warp * 32 + lane * 8)[0] = make_float4(acc[0], acc[1], acc[2], acc[3]);
            reinterpret_cast<float4*>(rq + warp * 32 + lane * 8)[1] = make_float4(acc[4], acc[5], acc[6], acc[7]);
        }
        cons_sync();
        if (tid < 16) {
            float qa = 0.f, qb = 0.f;
#pragma unroll
            for (int w = 0; w < 8; w++) { qa += rq[w * 32 + 2 * tid]; qb += rq[w * 32 + 2 * tid + 1]; }
            box_st1(&g_qbox[cta * 16 + tid], pack_bf16(qa, qb), epoch);
        }
        const unsigned long long* src = &g_qbox[grp * 512 + 2 * tid];
        unsigned long long qa, qb;
        unsigned n = 0;
        __nanosleep(300);
        while (true) {
            box_ld2(src, qa, qb);
            if ((uint32_t)(qa >> 32) == epoch && (uint32_t)(qb >> 32) == epoch) break;
            if (++n > SPIN_LIMIT) __trap();
            __nanosleep(100);
        }
        uint32_t* qs = reinterpret_cast<uint32_t*>(smem + OFF_Q);
        reinterpret_cast<uint2*>(qs)[tid] = make_uint2((uint32_t)qa, (uint32_t)qb);
        cons_sync();
#pragma unroll
        for (int ks = 0; ks < 8; ks++) {
            qf[ks][0] = qs[g * 64 + ks * 8 + t];
            qf[ks][1] = qs[g * 64 + ks * 8 + 4 + t];
        }
    }

    {
        float o[8][4];
#pragma unroll
        for (int i = 0; i < 8; i++) o[i][0] = o[i][1] = o[i][2] = o[i][3] = 0.f;
        float m0 = -INFINITY, m1 = -INFINITY, l0 = 0.f, l1 = 0.f;
        const int kw = (warp & 3) * 16, r7 = lane & 7, mi = lane >> 3;
        const uint32_t k_row = (kw + r7 + 8 * (mi & 1)) * 128;
        const uint32_t v_row = HALF_BYTES + (kw + r7 + 8 * (mi >> 1)) * 128;
        uint32_t k_off[4], v_off[4];
#pragma unroll
        for (int j = 0; j < 4; j++) {
            k_off[j] = k_row + (((2 * j + (mi >> 1)) ^ r7) << 4);
            v_off[j] = v_row + (((2 * j + (mi & 1)) ^ r7) << 4);
        }
        for (int n = KV0 + half; n < GU0; n += 2) {
            const int s = n % STAGES;
            const uint32_t ph = (n / STAGES) & 1;
            const uint32_t base = sbase + s * STAGE_BYTES;
            float sa[4] = {0.f, 0.f, 0.f, 0.f}, sb[4] = {0.f, 0.f, 0.f, 0.f};
            mbar_wait(bar_fullA + 8 * s, ph);
#pragma unroll
            for (int j = 0; j < 4; j++) {
                uint32_t a0, a1, a2, a3, c0, c1, c2, c3;
                ldsm4(base + k_off[j], a0, a1, a2, a3);
                ldsm4(base + k_off[j] + 8192, c0, c1, c2, c3);
                mma16816(sa, a0, a1, a2, a3, qf[j][0], qf[j][1]);
                mma16816(sb, c0, c1, c2, c3, qf[4 + j][0], qf[4 + j][1]);
            }
            const uint32_t r01 = pack_bf16(sa[0] + sb[0], sa[1] + sb[1]);
            const uint32_t r23 = pack_bf16(sa[2] + sb[2], sa[3] + sb[3]);
            const uint32_t u01 = pack_bf16(bf_lo(r01) * SM_SCALE, bf_hi(r01) * SM_SCALE);
            const uint32_t u23 = pack_bf16(bf_lo(r23) * SM_SCALE, bf_hi(r23) * SM_SCALE);
            const float s0 = bf_lo(u01), s1 = bf_hi(u01), s2 = bf_lo(u23), s3 = bf_hi(u23);
            float t0 = fmaxf(s0, s2), t1 = fmaxf(s1, s3);
#pragma unroll
            for (int sh = 4; sh <= 16; sh <<= 1) {
                t0 = fmaxf(t0, __shfl_xor_sync(0xffffffffu, t0, sh));
                t1 = fmaxf(t1, __shfl_xor_sync(0xffffffffu, t1, sh));
            }
            if (__any_sync(0xffffffffu, t0 > m0 || t1 > m1)) {
                const float n0 = fmaxf(m0, t0), n1 = fmaxf(m1, t1);
                const float f0 = ex2((m0 - n0) * LOG2E), f1 = ex2((m1 - n1) * LOG2E);
                m0 = n0; m1 = n1;
                l0 *= f0; l1 *= f1;
#pragma unroll
                for (int i = 0; i < 8; i++) { o[i][0] *= f0; o[i][1] *= f1; o[i][2] *= f0; o[i][3] *= f1; }
            }
            const float p0 = ex2((s0 - m0) * LOG2E), p1 = ex2((s1 - m1) * LOG2E);
            const float p2 = ex2((s2 - m0) * LOG2E), p3 = ex2((s3 - m1) * LOG2E);
            l0 += p0 + p2;
            l1 += p1 + p3;
            const uint32_t b0 = movm_t(pack_bf16(p0, p1));
            const uint32_t b1 = movm_t(pack_bf16(p2, p3));
            mbar_wait(bar_fullB + 8 * s, ph);
#pragma unroll
            for (int j = 0; j < 4; j++) {
                uint32_t a0, a1, a2, a3, c0, c1, c2, c3;
                ldsm4t(base + v_off[j], a0, a1, a2, a3);
                ldsm4t(base + v_off[j] + 8192, c0, c1, c2, c3);
                mma16816(o[j], a0, a1, a2, a3, b0, b1);
                mma16816(o[4 + j], c0, c1, c2, c3, b0, b1);
            }
            __syncwarp();
            if (lane == 0) mbar_arrive(bar_empty + 8 * s);
        }

        float* ms = reinterpret_cast<float*>(smem + OFF_MS);
        float* ls = reinterpret_cast<float*>(smem + OFF_LS);
        float* mrg = reinterpret_cast<float*>(smem + OFF_MRG);
        if (g == 0) reinterpret_cast<float2*>(ms + warp * 8)[t] = make_float2(m0, m1);
#pragma unroll
        for (int sh = 4; sh <= 16; sh <<= 1) {
            l0 += __shfl_xor_sync(0xffffffffu, l0, sh);
            l1 += __shfl_xor_sync(0xffffffffu, l1, sh);
        }
        cons_sync();
        float M0 = -INFINITY, M1 = -INFINITY;
#pragma unroll
        for (int w = 0; w < 8; w++) {
            const float2 v = reinterpret_cast<const float2*>(ms + w * 8)[t];
            M0 = fmaxf(M0, v.x); M1 = fmaxf(M1, v.y);
        }
        const float f0 = ex2((m0 - M0) * LOG2E), f1 = ex2((m1 - M1) * LOG2E);
        if (g == 0) reinterpret_cast<float2*>(ls + warp * 8)[t] = make_float2(l0 * f0, l1 * f1);
        float* dst = mrg + warp * MRG_WS + 2 * t * MRG_HS + g;
#pragma unroll
        for (int i = 0; i < 8; i++) {
            dst[16 * i] = o[i][0] * f0;
            dst[16 * i + MRG_HS] = o[i][1] * f1;
            dst[16 * i + 8] = o[i][2] * f0;
            dst[16 * i + 8 + MRG_HS] = o[i][3] * f1;
        }
        cons_sync();
        float a0 = 0.f, a1 = 0.f, a2 = 0.f, a3 = 0.f, L = 0.f, M = -INFINITY;
#pragma unroll
        for (int w = 0; w < 8; w++) {
            const float4 u = *reinterpret_cast<const float4*>(mrg + w * MRG_WS + warp * MRG_HS + 4 * lane);
            a0 += u.x; a1 += u.y; a2 += u.z; a3 += u.w;
            L += ls[w * 8 + warp];
            M = fmaxf(M, ms[w * 8 + warp]);
        }
        uint32_t* pb = &g_inbox[(grp * CPG + warp * 4) * BOX_WORDS + gj * P_REC];
        in_st4(pb + (lane >> 3) * BOX_WORDS + (lane & 7) * 4, pay(a0, tag), pay(a1, tag), pay(a2, tag), pay(a3, tag));
        if (lane < 8)
            in_st4(pb + (lane >> 1) * BOX_WORDS + 32 + (lane & 1) * 4, pay(M, tag), pay(L, tag), pay(M, tag), pay(L, tag));
        __syncwarp();
        if (lane == 0) mbar_arrive(bar_kv);
    }

    {
        float cg[7][4], cu[7][4];
#pragma unroll
        for (int i = 0; i < 7; i++) {
            cg[i][0] = cg[i][1] = cg[i][2] = cg[i][3] = 0.f;
            cu[i][0] = cu[i][1] = cu[i][2] = cu[i][3] = 0.f;
        }
        const int ks = warp & 1, mg = (warp >> 1) & 1, mi = lane >> 3;
        const uint32_t a_off = (ks * 16 + (lane & 7) + 8 * (mi >> 1)) * (FF_G * 2) + (mg * 14 + (mi & 1)) * 16;
        const uint32_t* xb = reinterpret_cast<const uint32_t*>(smem + OFF_XB) + kap * 64 + ks * 8 + t;
#pragma unroll
        for (int k = 0; k < 2; k++) {
            const int n = GU0 + 2 * k + half;
            const int s = n % STAGES;
            const uint32_t ph = (n / STAGES) & 1;
            const uint32_t a = sbase + s * STAGE_BYTES + a_off;
            const uint32_t b0 = xb[(n - GU0) * 16], b1 = xb[(n - GU0) * 16 + 4];
            mbar_wait(bar_fullA + 8 * s, ph);
#pragma unroll
            for (int i = 0; i < 7; i++) {
                uint32_t a0, a1, a2, a3;
                ldsm4t(a + i * 32, a0, a1, a2, a3);
                mma16816(cg[i], a0, a1, a2, a3, b0, b1);
            }
            mbar_wait(bar_fullB + 8 * s, ph);
#pragma unroll
            for (int i = 0; i < 7; i++) {
                uint32_t a0, a1, a2, a3;
                ldsm4t(a + HALF_BYTES + i * 32, a0, a1, a2, a3);
                mma16816(cu[i], a0, a1, a2, a3, b0, b1);
            }
            __syncwarp();
            if (lane == 0) mbar_arrive(bar_empty + 8 * s);
        }
        float* rg = reinterpret_cast<float*>(smem + OFF_REDG);
        if (t < 2) {
            float* dst = rg + (half * 2 + ks) * (2 * FF_G) + t * FF_G + mg * 112 + g;
#pragma unroll
            for (int i = 0; i < 7; i++) {
                dst[16 * i] = t ? cu[i][0] : cg[i][0];
                dst[16 * i + 8] = t ? cu[i][2] : cg[i][2];
            }
        }
        cons_sync();
        if (tid < 2 * FF_G / 4) {
            const float4* p = reinterpret_cast<const float4*>(rg) + tid;
            const float4 u0 = p[0], u1 = p[112], u2 = p[224], u3 = p[336];
            in_st4(&g_outbox[cta * OUT_WORDS + 4 * tid], pay((u0.x + u1.x) + (u2.x + u3.x), tag),
                   pay((u0.y + u1.y) + (u2.y + u3.y), tag), pay((u0.z + u1.z) + (u2.z + u3.z), tag),
                   pay((u0.w + u1.w) + (u2.w + u3.w), tag));
        }
    }

    {
        float c0[4] = {0.f, 0.f, 0.f, 0.f}, c1[4] = {0.f, 0.f, 0.f, 0.f};
        uint32_t* const dst = &g_inbox[((2 * warp + (t & 1)) * RG + kap) * BOX_WORDS + BOX_O + rho * 8 + g];
        const int mi = lane >> 3, r7 = lane & 7;
        const uint32_t l_off = r7 * 128 + (((2 * (warp & 3) + (mi & 1)) ^ r7) << 4) + (mi >> 1) * 1024;
        {
            const uint32_t* hb = &g_outbox[rho * RG * OUT_WORDS + min(tid, FF_G - 1)];
            const uint32_t* src = &g_outbox[(rho * RG + warp) * OUT_WORDS + OUT_O + lane];
            uint32_t gw[RG], uw[RG], w = tag ^ 1;
#pragma unroll
            for (int j = 0; j < RG; j++) gw[j] = uw[j] = w;
            unsigned n = 0;
            __nanosleep(800);
            while (true) {
                uint32_t bad = 0;
                if ((w ^ tag) & TAG_MASK) { bad = 1; w = in_ld1(src); }
#pragma unroll
                for (int j = 0; j < RG; j++) {
                    if (((gw[j] ^ tag) | (uw[j] ^ tag)) & TAG_MASK) {
                        bad = 1;
                        gw[j] = in_ld1(hb + j * OUT_WORDS);
                        uw[j] = in_ld1(hb + j * OUT_WORDS + FF_G);
                    }
                }
                if (!bad) break;
                if (++n > SPIN_LIMIT) __trap();
            }
            reinterpret_cast<uint16_t*>(smem + OFF_VEC)[vec_pos(tid >> 7, tid & 127)] = (uint16_t)(w >> 16);
            float gsum = 0.f, usum = 0.f;
#pragma unroll
            for (int j = 0; j < RG; j++) { gsum += val(gw[j]); usum += val(uw[j]); }
            const float gb = rbf(gsum), ub = rbf(usum);
            const float inner = 0.7978845608028654f * (gb + 0.044715f * gb * gb * gb);
            const float ge = rbf(0.5f * gb * (1.0f + tanhf(inner)));
            const int hi = tid >= 112;
            if (tid < FF_G)
                reinterpret_cast<__nv_bfloat16*>(smem + OFF_VEC)[vec_pos(2 + hi, tid - hi * 112)] = __float2bfloat16_rn(ge * ub);
            cons_sync();
        }
#pragma unroll 1
        for (int k = 0; k < 4; k++) {
            const int st = WO0 + k, s = st % STAGES, G = k < 2 ? 8 : 7;
            const uint32_t ph = (st / STAGES) & 1;
            const uint32_t vk = sbase + OFF_VEC + (k * 4 + t) * 64;
            const uint4 b0 = lds128(vk), b1 = lds128(vk + 16), b2 = lds128(vk + 32), b3 = lds128(vk + 48);
            const uint32_t ua = sbase + s * STAGE_BYTES + (warp >> 2) * (G * 1024) + l_off;
            const uint32_t ub = ua + HALF_BYTES - G * 1024;
            uint32_t a0, a1, a2, a3;
            mbar_wait(bar_fullA + 8 * s, ph);
            ldsm4t(ua, a0, a1, a2, a3);        mma16816(c0, a0, a1, a2, a3, b0.x, b0.y);
            ldsm4t(ua + 2048, a0, a1, a2, a3); mma16816(c1, a0, a1, a2, a3, b0.z, b0.w);
            ldsm4t(ua + 4096, a0, a1, a2, a3); mma16816(c0, a0, a1, a2, a3, b1.x, b1.y);
            mbar_wait(bar_fullB + 8 * s, ph);
            ldsm4t((6 + (mi >> 1) >= G ? ub : ua) + 6144, a0, a1, a2, a3); mma16816(c1, a0, a1, a2, a3, b1.z, b1.w);
            ldsm4t(ub + 8192, a0, a1, a2, a3);  mma16816(c0, a0, a1, a2, a3, b2.x, b2.y);
            ldsm4t(ub + 10240, a0, a1, a2, a3); mma16816(c1, a0, a1, a2, a3, b2.z, b2.w);
            ldsm4t(ub + 12288, a0, a1, a2, a3); mma16816(c0, a0, a1, a2, a3, b3.x, b3.y);
            if (k < 2) { ldsm4t(ub + 14336, a0, a1, a2, a3); mma16816(c1, a0, a1, a2, a3, b3.z, b3.w); }
            if (k == 3 && t < 2) in_st1(dst, pay(t ? c0[2] + c1[2] : c0[0] + c1[0], tag));
        }
        __syncwarp();
        if (lane == 0) mbar_arrive(bar_pub);
    }
    } else if (warp == 9) {
        const uint32_t epoch = epoch_raw + 1, tag = epoch & TAG_MASK;
        const int ocol = kap * 128 + rho * 8 + (lane & 1) * 4 + (lane >> 4) * 2 + ((lane >> 3) & 1);
        const float xres = __bfloat162float(x[ocol]);
        {
            const uint32_t e = tag ^ 8u;
#pragma unroll
            for (int i = 0; i < 4; i++)
                if (i * 128 + lane * 4 < OUT_WORDS) in_st4(&g_outbox[cta * OUT_WORDS + i * 128 + lane * 4], e, e, e, e);
            if (lane < 16) box_st1(&g_qbox[cta * 16 + lane], 0, epoch_raw);
        }
        asm volatile("bar.sync 2, 320;" ::: "memory");
        unsigned n = 0;
        mbar_wait(bar_kv, 0);
        {
            const uint32_t* src = inbox + lane * P_REC;
            uint4 a[8], ml;
            while (true) {
                ml = in_ld4(src + 32);
                if (tagged4(ml, tag)) break;
                if (++n > SPIN_LIMIT) __trap();
                __nanosleep(300);
            }
            while (true) {
#pragma unroll
                for (int i = 0; i < 8; i++) a[i] = in_ld4(src + 4 * i);
                bool ok = true;
#pragma unroll
                for (int i = 0; i < 8; i++) ok = ok && tagged4(a[i], tag);
                if (ok) break;
                if (++n > SPIN_LIMIT) __trap();
                __nanosleep(300);
            }
            __syncwarp();
            const float m = val(ml.x);
            int key = __float_as_int(m);
            key = key >= 0 ? key : key ^ 0x7fffffff;
            key = __reduce_max_sync(0xffffffffu, key);
            key = key >= 0 ? key : key ^ 0x7fffffff;
            const float wgt = ex2((m - __int_as_float(key)) * LOG2E);
            const float L = warp_sum(val(ml.y) * wgt);
            float v[32];
#pragma unroll
            for (int i = 0; i < 8; i++) {
                v[4 * i] = val(a[i].x) * wgt; v[4 * i + 1] = val(a[i].y) * wgt;
                v[4 * i + 2] = val(a[i].z) * wgt; v[4 * i + 3] = val(a[i].w) * wgt;
            }
            fold<16>(v, lane); fold<8>(v, lane); fold<4>(v, lane); fold<2>(v, lane); fold<1>(v, lane);
            const uint32_t ob = pack_bf16(0.f, __fdiv_rn(v[0], L));
            in_st1(&g_outbox[cta * OUT_WORDS + OUT_O + lane], ob | tag);
        }
        const uint32_t* src = inbox + BOX_O + lane * 4;
        uint4 a = in_ld4(src);
#pragma unroll 1
        for (int pass = 0; pass < 2; pass++) {
            if (pass) {
                while (!tagged4(a, tag) && !mbar_try_ns(bar_pub, 0, 1500)) {
                    a = in_ld4(src);
                    if (++n > SPIN_LIMIT) __trap();
                }
                while (!tagged4(a, tag)) {
                    a = in_ld4(src);
                    if (++n > SPIN_LIMIT) __trap();
                }
            }
            __syncwarp();
            const bool b4 = lane & 16, b3 = lane & 8;
            float v0 = (b4 ? val(a.z) : val(a.x)) + __shfl_xor_sync(0xffffffffu, b4 ? val(a.x) : val(a.z), 16);
            float v1 = (b4 ? val(a.w) : val(a.y)) + __shfl_xor_sync(0xffffffffu, b4 ? val(a.y) : val(a.w), 16);
            float r = (b3 ? v1 : v0) + __shfl_xor_sync(0xffffffffu, b3 ? v0 : v1, 8);
            r += __shfl_xor_sync(0xffffffffu, r, 4);
            r += __shfl_xor_sync(0xffffffffu, r, 2);
            if (pass && (lane & 6) == 0) out[ocol] = __float2bfloat16_rn(xres + r);
        }
        if (cta == 0 && lane == 0) g_epoch = epoch;
    } else {
        const int key0 = grp * S_K + gj * TILE_KEYS;
        uint64_t pol;
        asm volatile("createpolicy.fractional.L2::evict_first.b64 %0, 1.0;" : "=l"(pol));
        int4* tab = reinterpret_cast<int4*>(smem + OFF_TAB);
        for (int v = 4 + lane; v < 2 * N_STEPS; v += 32) {
            const int n = v >> 1, hb = v & 1;
            int4 e;
            if (n < GU0) e = make_int4(hb | (HALF_BYTES << 8), 0, key0 + (n - KV0) * (CPG * TILE_KEYS), 0);
            else if (n < WO0) e = make_int4((3 + hb) | (SMALL_BYTES << 8), rho * FF_G, kap * 128 + (n - GU0) * 32, 0);
            else if (n < DN0) e = make_int4(6 | (HALF_BYTES << 8), 0, rho * 256 + (v - 2 * WO0) * 64, 2 * kap);
            else e = make_int4(5 | (SMALL_BYTES << 8), 0, rho * FF_G + (v - 2 * DN0) * 56, 2 * kap);
            tab[v] = e;
        }
        if (lane == 0) {
#pragma unroll
            for (int s = 0; s < STAGES; s++) {
                if (s >= 2) {
                    mbar_init(bar_fullA + 8 * s, 1);
                    mbar_init(bar_fullB + 8 * s, 1);
                }
                mbar_init(bar_empty + 8 * s, 4);
            }
            mbar_init(bar_kv, 9);
            mbar_init(bar_pub, 8);
            asm volatile("fence.mbarrier_init.release.cluster;" ::: "memory");
            asm volatile("fence.proxy.async.shared::cta;" ::: "memory");
        } else if (lane < 7) {
            prefetch_tmap(&tm.k + (lane == 1 ? 0 : lane == 2 ? 1 : lane));
        }
        __syncwarp();
        asm volatile("bar.arrive 2, 320;" ::: "memory");
        if (lane == 0) {
            constexpr int N_COUNTS = (CNT1 - CNT0) / 2 + 1;
            asm volatile("red.relaxed.gpu.global.add.u32 [%0], 1;" ::"l"(&g_count) : "memory");
            int landed = 0, next = CNT0, mine = NCTA + NCTA / 2, win = WIN;
            for (int v = 4; v < 2 * N_STEPS || next < CNT1; v++) {
                const bool go = v < 2 * N_STEPS;
                const int n = v >> 1, s = n % STAGES, hb = v & 1;
                const int4 e = tab[go ? v : 4];
                const uint32_t bar = (hb ? bar_fullB : bar_fullA) + 8 * s;
                if (go && !hb && n >= STAGES) mbar_wait(bar_empty + 8 * s, ((n / STAGES) & 1) ^ 1);
                while (landed <= v - win) {
                    const int wn = landed >> 1;
                    mbar_wait(((landed & 1) ? bar_fullB : bar_fullA) + 8 * (wn % STAGES), (wn / STAGES) & 1);
                    landed++;
                }
                if (go) {
                    mbar_expect_tx(bar, e.x >> 8);
                    tma3d(sbase + s * STAGE_BYTES + hb * HALF_BYTES, &tm.k + (e.x & 7), e.y, e.z, e.w, bar, pol);
                    if (v == V_COMBINE) mbar_arrive(bar_kv);
                }
                if (landed > next && next < CNT1) {
                    const uint32_t seen = atomicAdd(&g_count, 1u) - epoch_raw * (uint32_t)(NCTA * N_COUNTS);
                    const int lead = mine - (int)seen;
                    win = lead > (landed >= 2 * WO0 - 4 ? LEAD_END : LEAD_HI) ? WIN - 1 : (lead < -LEAD_LO ? WIN + 1 : WIN);
                    if (landed >= WIDE0 && landed < WIDE1) win++;
                    mine += NCTA;
                    next += 2;
                }
            }
        }
    }
}

typedef CUresult (*EncodeFn)(CUtensorMap*, CUtensorMapDataType, cuuint32_t, void*, const cuuint64_t*, const cuuint64_t*,
                             const cuuint32_t*, const cuuint32_t*, CUtensorMapInterleave, CUtensorMapSwizzle,
                             CUtensorMapL2promotion, CUtensorMapFloatOOBfill);

void map_blocks(EncodeFn enc, CUtensorMap* m, void* p, uint64_t rows, uint32_t row_elems, uint32_t box_rows) {
    const cuuint64_t gd[3] = {64, rows, row_elems / 64};
    const cuuint64_t gs[2] = {(cuuint64_t)row_elems * 2, 128};
    const cuuint32_t bd[3] = {64, box_rows, 2};
    const cuuint32_t es[3] = {1, 1, 1};
    enc(m, CU_TENSOR_MAP_DATA_TYPE_BFLOAT16, 3, p, gd, gs, bd, es, CU_TENSOR_MAP_INTERLEAVE_NONE,
        CU_TENSOR_MAP_SWIZZLE_128B, CU_TENSOR_MAP_L2_PROMOTION_L2_256B, CU_TENSOR_MAP_FLOAT_OOB_FILL_NONE);
}
void map_cols(EncodeFn enc, CUtensorMap* m, void* p, int rank, uint64_t cols, uint32_t box_cols, uint32_t box_rows) {
    const cuuint64_t gd[3] = {cols, D_MODEL, 1};
    const cuuint64_t gs[2] = {cols * 2, cols * 2 * D_MODEL};
    const cuuint32_t bd[3] = {box_cols, box_rows, 1};
    const cuuint32_t es[3] = {1, 1, 1};
    enc(m, CU_TENSOR_MAP_DATA_TYPE_BFLOAT16, rank, p, gd, gs, bd, es, CU_TENSOR_MAP_INTERLEAVE_NONE,
        CU_TENSOR_MAP_SWIZZLE_NONE, CU_TENSOR_MAP_L2_PROMOTION_L2_128B, CU_TENSOR_MAP_FLOAT_OOB_FILL_NONE);
}

}

extern "C" void kernel_launch(void* const* d_in, const int* in_sizes, int n_in, void* d_out, int out_size) {
    (void)in_sizes; (void)n_in; (void)out_size;
    static EncodeFn encode = nullptr;
    if (!encode) {
        void* fn = nullptr;
        cudaDriverEntryPointQueryResult qr;
        cudaGetDriverEntryPoint("cuTensorMapEncodeTiled", &fn, cudaEnableDefault, &qr);
        encode = (EncodeFn)fn;
        cudaFuncSetAttribute(fused_decode_kernel, cudaFuncAttributeMaxDynamicSharedMemorySize, SMEM_BYTES);
    }
    Maps tm;
    map_blocks(encode, &tm.k, d_in[1], (uint64_t)N_HKV * S_K, 128, TILE_KEYS);
    map_blocks(encode, &tm.v, d_in[2], (uint64_t)N_HKV * S_K, 128, TILE_KEYS);
    map_cols(encode, &tm.q, d_in[3], 2, QCOLS, 32, 256);
    map_cols(encode, &tm.g, d_in[6], 3, D_FF, FF_G, 32);
    map_cols(encode, &tm.u, d_in[7], 3, D_FF, FF_G, 32);
    map_blocks(encode, &tm.d, d_in[8], D_FF, D_MODEL, 56);
    map_blocks(encode, &tm.o, d_in[4], QCOLS, D_MODEL, 64);
    fused_decode_kernel<<<NCTA, NTHREADS, SMEM_BYTES, cudaStreamPerThread>>>(
        (const __nv_bfloat16*)d_in[1], (const __nv_bfloat16*)d_in[0], (__nv_bfloat16*)d_out, tm);
}
```
